```python
import torch

def _softmax(x, axis=-1):
    return torch.softmax(x, dim=axis)
def _gelu(x):
    return torch.nn.functional.gelu(x, approximate="tanh")
def _silu(x):
    return torch.nn.functional.silu(x)
def _sigmoid(x):
    return torch.sigmoid(x)
def _layernorm(x, axis=-1, eps=1e-5):
    m = x.mean(dim=axis, keepdim=True)
    v = x.var(dim=axis, keepdim=True, unbiased=False)
    return (x - m) / torch.sqrt(v + eps)
def _scatter_add(tgt, idx, src, axis=0):
    return tgt.clone().index_add_(axis, idx, src)
def _segment_sum(src, seg, n):
    out = torch.zeros((n,) + src.shape[1:], dtype=src.dtype)
    return out.index_add_(0, seg, src)
def _pad(x, pw):
    flat = tuple(v for pair in reversed(pw) for v in pair)
    return torch.nn.functional.pad(x, flat)

kernel_name = 'concat_heads__gqa_block_cached__gqa_block_cached__near_ridge'

def setup_inputs():

    _w = (lambda a: (lambda t: t.to(torch.bfloat16) if t.is_floating_point() else t)(torch.as_tensor(a)))
    def _A_setup():
        B, Sq, D = 8, 80, 448
        Hq, Hkv, Sk, Dh = 16, 8, 1024, 256
        assert Hq % Hkv == 0, (Hq, Hkv)
        return {
            "x": _w((lambda *s: torch.randn(*s, dtype=torch.bfloat16) * 0.8)(B, Sq, D)),
            "k_cache": _w((lambda *s: torch.randn(*s, dtype=torch.bfloat16) * 0.8)(B, Hkv, Sk, Dh)),
            "v_cache": _w((lambda *s: torch.randn(*s, dtype=torch.bfloat16) * 0.05)(B, Hkv, Sk, Dh)),
            "wq": _w((lambda *s: torch.randn(*s, dtype=torch.bfloat16) * 0.8)(D, Hq * Dh) * (D ** -0.5)),
            "wo": _w((lambda *s: torch.randn(*s, dtype=torch.bfloat16) * 0.05)(Hq * Dh, D) * ((Hq * Dh) ** -0.5)),
        }
    _A_in = _A_setup()

    def _B_setup():
        B, Sq, D = 8, 80, 448
        Hq, Hkv, Sk, Dh = 16, 8, 1024, 256
        assert Hq % Hkv == 0, (Hq, Hkv)
        return {
            "x": _w((lambda *s: torch.randn(*s, dtype=torch.bfloat16) * 0.8)(B, Sq, D)),
            "k_cache": _w((lambda *s: torch.randn(*s, dtype=torch.bfloat16) * 0.8)(B, Hkv, Sk, Dh)),
            "v_cache": _w((lambda *s: torch.randn(*s, dtype=torch.bfloat16) * 0.05)(B, Hkv, Sk, Dh)),
            "wq": _w((lambda *s: torch.randn(*s, dtype=torch.bfloat16) * 0.8)(D, Hq * Dh) * (D ** -0.5)),
            "wo": _w((lambda *s: torch.randn(*s, dtype=torch.bfloat16) * 0.05)(Hq * Dh, D) * ((Hq * Dh) ** -0.5)),
        }
    _B_in = _B_setup()

    return {
        "A_x": _A_in["x"],
        "A_k_cache": _A_in["k_cache"],
        "A_v_cache": _A_in["v_cache"],
        "A_wq": _A_in["wq"],
        "A_wo": _A_in["wo"],
        "B_x": _B_in["x"],
        "B_k_cache": _B_in["k_cache"],
        "B_v_cache": _B_in["v_cache"],
        "B_wq": _B_in["wq"],
        "B_wo": _B_in["wo"],
    }

def reference(A_x, A_k_cache, A_v_cache, A_wq, A_wo, B_x, B_k_cache, B_v_cache, B_wq, B_wo):
    def _A_ref(x, k_cache, v_cache, wq, wo):
        B, Sq, D = x.shape
        Hq, Dh = 16, 256
        Hkv = k_cache.shape[1]
        rep = Hq // Hkv
        q = (lambda x, *d: x.permute(*d))((x @ wq).reshape(B, Sq, Hq, Dh), 0, 2, 1, 3)
        k = (lambda x, n, axis: torch.repeat_interleave(x, n, dim=axis))(k_cache, rep, axis=1)
        v = (lambda x, n, axis: torch.repeat_interleave(x, n, dim=axis))(v_cache, rep, axis=1)
        scores = torch.einsum("bhqd,bhkd->bhqk", q, k) * (Dh ** -0.5)
        p = _softmax(scores, axis=-1)
        o = torch.einsum("bhqk,bhkd->bhqd", p, v)
        return (lambda x, *d: x.permute(*d))(o, 0, 2, 1, 3).reshape(B, Sq, Hq * Dh) @ wo

    def _B_ref(x, k_cache, v_cache, wq, wo):
        B, Sq, D = x.shape
        Hq, Dh = 16, 256
        Hkv = k_cache.shape[1]
        rep = Hq // Hkv
        q = (lambda x, *d: x.permute(*d))((x @ wq).reshape(B, Sq, Hq, Dh), 0, 2, 1, 3)
        k = (lambda x, n, axis: torch.repeat_interleave(x, n, dim=axis))(k_cache, rep, axis=1)
        v = (lambda x, n, axis: torch.repeat_interleave(x, n, dim=axis))(v_cache, rep, axis=1)
        scores = torch.einsum("bhqd,bhkd->bhqk", q, k) * (Dh ** -0.5)
        p = _softmax(scores, axis=-1)
        o = torch.einsum("bhqk,bhkd->bhqd", p, v)
        return (lambda x, *d: x.permute(*d))(o, 0, 2, 1, 3).reshape(B, Sq, Hq * Dh) @ wo

    a = _A_ref(A_x, A_k_cache, A_v_cache, A_wq, A_wo)
    b = _B_ref(B_x, B_k_cache, B_v_cache, B_wq, B_wo)
    return torch.concatenate([a, b], axis=-1)
```

```cpp
#include <cuda_runtime.h>
#include <cuda_bf16.h>
#include <cuda.h>
#include <stdint.h>

namespace {

constexpr int NCTA = 128;
constexpr int NTHREADS = 512;

constexpr uint32_t SB = 0x400;
constexpr uint32_t OFF_Q     = 0;
constexpr uint32_t QCHUNK    = 20480;
constexpr uint32_t OFF_SLOT  = 81920;
constexpr uint32_t SLOT_B    = 32768;
constexpr uint32_t OFF_P     = OFF_SLOT + 3 * SLOT_B;
constexpr uint32_t OFF_W     = OFF_SLOT + 2 * SLOT_B;
constexpr uint32_t WST_B     = 16384;
constexpr uint32_t OFF_SC    = OFF_P + 2 * QCHUNK;
constexpr uint32_t OFF_FLAG  = OFF_SC + 1280;
constexpr uint32_t OFF_BAR   = OFF_FLAG + 32;
constexpr uint32_t BAR_FULL  = OFF_BAR;
constexpr uint32_t BAR_EMPTY = BAR_FULL + 32;
constexpr uint32_t BAR_WFULL = BAR_EMPTY + 32;
constexpr uint32_t BAR_WEMPT = BAR_WFULL + 32;
constexpr uint32_t BAR_X     = BAR_WEMPT + 32;
constexpr uint32_t BAR_T     = BAR_X + 8;
constexpr uint32_t BAR_PW    = BAR_T + 8;
constexpr uint32_t OFF_MISC  = BAR_PW + 56;
constexpr uint32_t OFF_PROF  = OFF_MISC + 16;
constexpr uint32_t SMEM_USED = OFF_PROF + 256;
constexpr uint32_t SMEM_BYTES = SMEM_USED;

#define SREG_STR "setmaxnreg.dec.sync.aligned.u32 104;"
#define WITH_O 1
#define PACE_TAU 0
#define PACE_T0 5000
#define NO_RED 0
#define NO_ST 0
#define POLL_NS 100
#define K0_AT 8
#define K_STEP 2
#define WO_AT 99
#define KV_POL "evict_first"

struct Maps {
  CUtensorMap m[10];
  CUtensorMap k8[2];
};

__device__ uint4 g_part[16 * 8 * 7 * 640];
__device__ unsigned int g_ticket;
#define PT(idx) do {} while (0)
#define PS(idx) do {} while (0)
#define PO(idx) do {} while (0)
#define PROF(idx) do {} while (0)

__device__ __forceinline__ void mbar_init(uint32_t bar, uint32_t cnt) {
  asm volatile("mbarrier.init.shared::cta.b64 [%0], %1;" ::"r"(bar), "r"(cnt) : "memory");
}
__device__ __forceinline__ void mbar_expect_tx(uint32_t bar, uint32_t bytes) {
  asm volatile("mbarrier.arrive.expect_tx.shared::cta.b64 _, [%0], %1;" ::"r"(bar), "r"(bytes) : "memory");
}
__device__ __forceinline__ void mbar_arrive(uint32_t bar) {
  asm volatile("mbarrier.arrive.shared::cta.b64 _, [%0];" ::"r"(bar) : "memory");
}
__device__ __forceinline__ void mbar_arrive_n(uint32_t bar, uint32_t n) {
  asm volatile("mbarrier.arrive.shared::cta.b64 _, [%0], %1;" ::"r"(bar), "r"(n) : "memory");
}
__device__ __forceinline__ void mbar_wait(uint32_t bar, uint32_t parity) {
  asm volatile(
      "{\n.reg .pred p;\n.reg .u32 c;\nmov.u32 c, 0;\n"
      "W_LOOP:\n"
      "mbarrier.try_wait.parity.shared::cta.b64 p, [%0], %1, 2000;\n"
      "@p bra W_DONE;\n"
      "add.u32 c, c, 1;\n"
      "setp.lt.u32 p, c, 0x100000;\n"
      "@p bra W_LOOP;\n"
      "trap;\n"
      "W_DONE:\n}\n" ::"r"(bar), "r"(parity) : "memory");
}
__device__ __forceinline__ void nb_sync(uint32_t id, uint32_t n) { asm volatile("bar.sync %0, %1;" ::"r"(id), "r"(n) : "memory"); }
__device__ __forceinline__ void nb_arrive(uint32_t id, uint32_t n) { asm volatile("bar.arrive %0, %1;" ::"r"(id), "r"(n) : "memory"); }
constexpr uint32_t NB_O = 1, NB_PFULL = 2, NB_PEMPTY = 4, NB_GO = 6, NB_Q = 8, NB_ORD = 10;
__device__ __forceinline__ void tma3d(uint32_t dst, const CUtensorMap* m, int c1, int c2, uint32_t bar) {
  asm volatile(
      "cp.async.bulk.tensor.3d.shared::cluster.global.mbarrier::complete_tx::bytes [%0], [%1, {%2, %3, %4}], [%5];"
      ::"r"(dst), "l"(m), "r"(0), "r"(c1), "r"(c2), "r"(bar) : "memory");
}
__device__ __forceinline__ void tma3d_ef(uint32_t dst, const CUtensorMap* m, int c1, int c2, uint32_t bar, uint64_t pol) {
  asm volatile(
      "cp.async.bulk.tensor.3d.shared::cluster.global.mbarrier::complete_tx::bytes.L2::cache_hint [%0], [%1, {%2, %3, %4}], [%5], %6;"
      ::"r"(dst), "l"(m), "r"(0), "r"(c1), "r"(c2), "r"(bar), "l"(pol) : "memory");
}
__device__ __forceinline__ void tma3d_pf(const CUtensorMap* m, int c1, int c2) {
  asm volatile("cp.async.bulk.prefetch.tensor.3d.L2.global [%0, {%1, %2, %3}];" ::"l"(m), "r"(0), "r"(c1), "r"(c2)
               : "memory");
}
__device__ __forceinline__ void wg_fence() { asm volatile("wgmma.fence.sync.aligned;" ::: "memory"); }
__device__ __forceinline__ void wg_commit() { asm volatile("wgmma.commit_group.sync.aligned;" ::: "memory"); }
template <int N>
__device__ __forceinline__ void wg_wait() { asm volatile("wgmma.wait_group.sync.aligned %0;" ::"n"(N) : "memory"); }
__device__ __forceinline__ void fence_async() { asm volatile("fence.proxy.async.shared::cta;" ::: "memory"); }
template <int N>
__device__ __forceinline__ void reg_fence(float* d) {
#pragma unroll
  for (int i = 0; i < N; i++) asm volatile("" : "+f"(d[i])::"memory");
}
__device__ __forceinline__ constexpr uint32_t dlo(uint32_t saddr) { return ((saddr & 0x3FFFFu) >> 4) | (1u << 16); }
template <int V>
struct IC { static constexpr int value = V; };
template <int I, int N, class F>
__device__ __forceinline__ void static_for(F&& f) {
  if constexpr (I < N) {
    f(IC<I>{});
    static_for<I + 1, N>(f);
  }
}
__device__ __forceinline__ uint32_t pack_bf16(float lo, float hi) {
  uint32_t r;
  asm("cvt.rn.bf16x2.f32 %0, %1, %2;" : "=r"(r) : "f"(hi), "f"(lo));
  return r;
}
template <uint32_t XR, uint32_t OFF>
__device__ __forceinline__ void stsm4_o(uint32_t a, uint32_t r0, uint32_t r1, uint32_t r2, uint32_t r3) {
  asm volatile("{\n.reg .b32 t;\nxor.b32 t, %0, %6;\nstmatrix.sync.aligned.m8n8.x4.shared.b16 [t + %5], {%1, %2, %3, %4};\n}\n"
               ::"r"(a), "r"(r0), "r"(r1), "r"(r2), "r"(r3), "n"(OFF), "n"(XR) : "memory");
}
__device__ __forceinline__ void stsm4t(uint32_t a, uint32_t r0, uint32_t r1, uint32_t r2, uint32_t r3) {
  asm volatile("stmatrix.sync.aligned.m8n8.x4.trans.shared.b16 [%0], {%1, %2, %3, %4};" ::"r"(a), "r"(r0), "r"(r1),
               "r"(r2), "r"(r3) : "memory");
}
__device__ __forceinline__ float ex2(float x) {
  float y;
  asm("ex2.approx.ftz.f32 %0, %1;" : "=f"(y) : "f"(x));
  return y;
}
__device__ __forceinline__ float4 lds128(uint32_t a) {
  float4 v;
  asm volatile("ld.shared.v4.f32 {%0, %1, %2, %3}, [%4];" : "=f"(v.x), "=f"(v.y), "=f"(v.z), "=f"(v.w) : "r"(a) : "memory");
  return v;
}
__device__ __forceinline__ void sts32(uint32_t a, float v) {
  asm volatile("st.shared.f32 [%0], %1;" ::"r"(a), "f"(v) : "memory");
}
__device__ __forceinline__ uint4 ld_relaxed128(const uint4* p) {
  uint4 v;
  asm volatile("{\n.reg .b128 t;\nld.relaxed.gpu.global.b128 t, [%4];\nmov.b128 {%0, %1, %2, %3}, t;\n}\n"
               : "=r"(v.x), "=r"(v.y), "=r"(v.z), "=r"(v.w) : "l"(p) : "memory");
  return v;
}
__device__ __forceinline__ void st_relaxed128(uint4* p, uint32_t a, uint32_t b, uint32_t c, uint32_t d) {
  asm volatile("{\n.reg .b128 t;\nmov.b128 t, {%1, %2, %3, %4};\nst.relaxed.gpu.global.b128 [%0], t;\n}\n" ::"l"(p),
               "r"(a), "r"(b), "r"(c), "r"(d) : "memory");
}
__device__ __forceinline__ float bf_lo(uint32_t w) { return __uint_as_float(w << 16); }
__device__ __forceinline__ float bf_hi(uint32_t w) { return __uint_as_float(w & 0xffff0000u); }

template <uint32_t OA, uint32_t OB, uint32_t HIA = 0x40000040u>
__device__ __forceinline__ void wgmma_n64_kk_z(float* d, uint32_t a, uint32_t b) {
  asm volatile(
      "{\n.reg .b32 ta, tb;\n.reg .b64 da, db;\nadd.u32 ta, %32, %34;\nadd.u32 tb, %33, %35;\nmov.b64 da, {ta, %36};\nmov.b64 db, {tb, 0x40000040};\n"
      "wgmma.mma_async.sync.aligned.m64n64k16.f32.bf16.bf16 {"
      "%0, %1, %2, %3, %4, %5, %6, %7, %8, %9, %10, %11, %12, %13, %14, %15,"
      "%16, %17, %18, %19, %20, %21, %22, %23, %24, %25, %26, %27, %28, %29, %30, %31}, da, db, 0, 1, 1, 0, 0;\n}\n"
      : "=f"(d[0]), "=f"(d[1]), "=f"(d[2]), "=f"(d[3]), "=f"(d[4]), "=f"(d[5]), "=f"(d[6]), "=f"(d[7]),
        "=f"(d[8]), "=f"(d[9]), "=f"(d[10]), "=f"(d[11]), "=f"(d[12]), "=f"(d[13]), "=f"(d[14]), "=f"(d[15]),
        "=f"(d[16]), "=f"(d[17]), "=f"(d[18]), "=f"(d[19]), "=f"(d[20]), "=f"(d[21]), "=f"(d[22]), "=f"(d[23]),
        "=f"(d[24]), "=f"(d[25]), "=f"(d[26]), "=f"(d[27]), "=f"(d[28]), "=f"(d[29]), "=f"(d[30]), "=f"(d[31])
      : "r"(a), "r"(b), "n"(OA >> 4), "n"(OB >> 4), "n"(HIA));
}

template <uint32_t OA, uint32_t OB, uint32_t HIA = 0x40000040u>
__device__ __forceinline__ void wgmma_n64_kk(float* d, uint32_t a, uint32_t b) {
  asm volatile(
      "{\n.reg .b32 ta, tb;\n.reg .b64 da, db;\nadd.u32 ta, %32, %34;\nadd.u32 tb, %33, %35;\nmov.b64 da, {ta, %36};\nmov.b64 db, {tb, 0x40000040};\n"
      "wgmma.mma_async.sync.aligned.m64n64k16.f32.bf16.bf16 {"
      "%0, %1, %2, %3, %4, %5, %6, %7, %8, %9, %10, %11, %12, %13, %14, %15,"
      "%16, %17, %18, %19, %20, %21, %22, %23, %24, %25, %26, %27, %28, %29, %30, %31}, da, db, 1, 1, 1, 0, 0;\n}\n"
      : "+f"(d[0]), "+f"(d[1]), "+f"(d[2]), "+f"(d[3]), "+f"(d[4]), "+f"(d[5]), "+f"(d[6]), "+f"(d[7]),
        "+f"(d[8]), "+f"(d[9]), "+f"(d[10]), "+f"(d[11]), "+f"(d[12]), "+f"(d[13]), "+f"(d[14]), "+f"(d[15]),
        "+f"(d[16]), "+f"(d[17]), "+f"(d[18]), "+f"(d[19]), "+f"(d[20]), "+f"(d[21]), "+f"(d[22]), "+f"(d[23]),
        "+f"(d[24]), "+f"(d[25]), "+f"(d[26]), "+f"(d[27]), "+f"(d[28]), "+f"(d[29]), "+f"(d[30]), "+f"(d[31])
      : "r"(a), "r"(b), "n"(OA >> 4), "n"(OB >> 4), "n"(HIA));
}

template <uint32_t OA, uint32_t OB, uint32_t HIA = 0x40000040u>
__device__ __forceinline__ void wgmma_n80_mk_z(float* d, uint32_t a, uint32_t b) {
  asm volatile(
      "{\n.reg .b32 ta, tb;\n.reg .b64 da, db;\nadd.u32 ta, %40, %42;\nadd.u32 tb, %41, %43;\nmov.b64 da, {ta, %44};\nmov.b64 db, {tb, 0x40000040};\n"
      "wgmma.mma_async.sync.aligned.m64n80k16.f32.bf16.bf16 {"
      "%0, %1, %2, %3, %4, %5, %6, %7, %8, %9, %10, %11, %12, %13, %14, %15,"
      "%16, %17, %18, %19, %20, %21, %22, %23, %24, %25, %26, %27, %28, %29, %30, %31,"
      "%32, %33, %34, %35, %36, %37, %38, %39}, da, db, 0, 1, 1, 1, 0;\n}\n"
      : "=f"(d[0]), "=f"(d[1]), "=f"(d[2]), "=f"(d[3]), "=f"(d[4]), "=f"(d[5]), "=f"(d[6]), "=f"(d[7]),
        "=f"(d[8]), "=f"(d[9]), "=f"(d[10]), "=f"(d[11]), "=f"(d[12]), "=f"(d[13]), "=f"(d[14]), "=f"(d[15]),
        "=f"(d[16]), "=f"(d[17]), "=f"(d[18]), "=f"(d[19]), "=f"(d[20]), "=f"(d[21]), "=f"(d[22]), "=f"(d[23]),
        "=f"(d[24]), "=f"(d[25]), "=f"(d[26]), "=f"(d[27]), "=f"(d[28]), "=f"(d[29]), "=f"(d[30]), "=f"(d[31]),
        "=f"(d[32]), "=f"(d[33]), "=f"(d[34]), "=f"(d[35]), "=f"(d[36]), "=f"(d[37]), "=f"(d[38]), "=f"(d[39])
      : "r"(a), "r"(b), "n"(OA >> 4), "n"(OB >> 4), "n"(HIA));
}

template <uint32_t OA, uint32_t OB, uint32_t HIA = 0x40000040u>
__device__ __forceinline__ void wgmma_n80_mk1(float* d, uint32_t a, uint32_t b) {
  asm volatile(
      "{\n.reg .b32 ta, tb;\n.reg .b64 da, db;\nadd.u32 ta, %40, %42;\nadd.u32 tb, %41, %43;\nmov.b64 da, {ta, %44};\nmov.b64 db, {tb, 0x40000040};\n"
      "wgmma.mma_async.sync.aligned.m64n80k16.f32.bf16.bf16 {"
      "%0, %1, %2, %3, %4, %5, %6, %7, %8, %9, %10, %11, %12, %13, %14, %15,"
      "%16, %17, %18, %19, %20, %21, %22, %23, %24, %25, %26, %27, %28, %29, %30, %31,"
      "%32, %33, %34, %35, %36, %37, %38, %39}, da, db, 1, 1, 1, 1, 0;\n}\n"
      : "+f"(d[0]), "+f"(d[1]), "+f"(d[2]), "+f"(d[3]), "+f"(d[4]), "+f"(d[5]), "+f"(d[6]), "+f"(d[7]),
        "+f"(d[8]), "+f"(d[9]), "+f"(d[10]), "+f"(d[11]), "+f"(d[12]), "+f"(d[13]), "+f"(d[14]), "+f"(d[15]),
        "+f"(d[16]), "+f"(d[17]), "+f"(d[18]), "+f"(d[19]), "+f"(d[20]), "+f"(d[21]), "+f"(d[22]), "+f"(d[23]),
        "+f"(d[24]), "+f"(d[25]), "+f"(d[26]), "+f"(d[27]), "+f"(d[28]), "+f"(d[29]), "+f"(d[30]), "+f"(d[31]),
        "+f"(d[32]), "+f"(d[33]), "+f"(d[34]), "+f"(d[35]), "+f"(d[36]), "+f"(d[37]), "+f"(d[38]), "+f"(d[39])
      : "r"(a), "r"(b), "n"(OA >> 4), "n"(OB >> 4), "n"(HIA));
}

template <uint32_t OA, uint32_t OB, uint32_t HIA = 0x40000040u>
__device__ __forceinline__ void wgmma_n160_mk1(float* d, uint32_t a, uint32_t b) {
  asm volatile(
      "{\n.reg .b32 ta, tb;\n.reg .b64 da, db;\nadd.u32 ta, %80, %82;\nadd.u32 tb, %81, %83;\nmov.b64 da, {ta, %84};\nmov.b64 db, {tb, 0x40000040};\n"
      "wgmma.mma_async.sync.aligned.m64n160k16.f32.bf16.bf16 {"
      "%0, %1, %2, %3, %4, %5, %6, %7, %8, %9, %10, %11, %12, %13, %14, %15,"
      "%16, %17, %18, %19, %20, %21, %22, %23, %24, %25, %26, %27, %28, %29, %30, %31,"
      "%32, %33, %34, %35, %36, %37, %38, %39, %40, %41, %42, %43, %44, %45, %46, %47,"
      "%48, %49, %50, %51, %52, %53, %54, %55, %56, %57, %58, %59, %60, %61, %62, %63,"
      "%64, %65, %66, %67, %68, %69, %70, %71, %72, %73, %74, %75, %76, %77, %78, %79}, da, db, 1, 1, 1, 1, 0;\n}\n"
      : "+f"(d[0]), "+f"(d[1]), "+f"(d[2]), "+f"(d[3]), "+f"(d[4]), "+f"(d[5]), "+f"(d[6]), "+f"(d[7]),
        "+f"(d[8]), "+f"(d[9]), "+f"(d[10]), "+f"(d[11]), "+f"(d[12]), "+f"(d[13]), "+f"(d[14]), "+f"(d[15]),
        "+f"(d[16]), "+f"(d[17]), "+f"(d[18]), "+f"(d[19]), "+f"(d[20]), "+f"(d[21]), "+f"(d[22]), "+f"(d[23]),
        "+f"(d[24]), "+f"(d[25]), "+f"(d[26]), "+f"(d[27]), "+f"(d[28]), "+f"(d[29]), "+f"(d[30]), "+f"(d[31]),
        "+f"(d[32]), "+f"(d[33]), "+f"(d[34]), "+f"(d[35]), "+f"(d[36]), "+f"(d[37]), "+f"(d[38]), "+f"(d[39]),
        "+f"(d[40]), "+f"(d[41]), "+f"(d[42]), "+f"(d[43]), "+f"(d[44]), "+f"(d[45]), "+f"(d[46]), "+f"(d[47]),
        "+f"(d[48]), "+f"(d[49]), "+f"(d[50]), "+f"(d[51]), "+f"(d[52]), "+f"(d[53]), "+f"(d[54]), "+f"(d[55]),
        "+f"(d[56]), "+f"(d[57]), "+f"(d[58]), "+f"(d[59]), "+f"(d[60]), "+f"(d[61]), "+f"(d[62]), "+f"(d[63]),
        "+f"(d[64]), "+f"(d[65]), "+f"(d[66]), "+f"(d[67]), "+f"(d[68]), "+f"(d[69]), "+f"(d[70]), "+f"(d[71]),
        "+f"(d[72]), "+f"(d[73]), "+f"(d[74]), "+f"(d[75]), "+f"(d[76]), "+f"(d[77]), "+f"(d[78]), "+f"(d[79])
      : "r"(a), "r"(b), "n"(OA >> 4), "n"(OB >> 4), "n"(HIA));
}

__device__ __forceinline__ void kv_slot(int i, uint32_t& slot, uint32_t& use) {
  use = (uint32_t)i / 3u;
  slot = (uint32_t)i - use * 3u;
}
__device__ __forceinline__ void wo_slot(int u, uint32_t& slot, uint32_t& use) {
  uint32_t r = u & 3, q = u >> 2;
  slot = (r == 0) ? 2u : (r == 3) ? 3u : (r - 1u);
  use = q + ((r == 0) ? 10u : (r == 3) ? 0u : 11u);
}

struct SCtx {
  uint32_t pa01, pa2, sa01, sa2;
  bool wr;
};

template <int BLK>
__device__ __forceinline__ void qk_issue(float* s, uint32_t dk) {
  constexpr uint32_t dq = dlo(SB + OFF_Q + BLK * 8192);
  constexpr uint32_t HI = (BLK == 2) ? 0x40000020u : 0x40000040u;
  wg_fence();
  constexpr uint32_t T = BLK << 20;
  wgmma_n64_kk_z<0, T, HI>(s, dq, dk);
  static_for<1, 16>([&](auto I) {
    constexpr int ks = decltype(I)::value;
    wgmma_n64_kk<(ks >> 2) * QCHUNK + (ks & 3) * 32, T + (ks >> 2) * 8192 + (ks & 3) * 32, HI>(s, dq, dk);
  });
  wg_commit();
}

template <int BLK, int PB, bool LAST>
__device__ __forceinline__ void softmax_blk(float* s, float* mc, float* l, uint32_t& flag, const SCtx& cx) {
  constexpr float c = 0.0625f * 1.4426950408889634f;
  constexpr int NR = (BLK == 2) ? 1 : 2;
  float mx[NR], alpha[NR];
  bool need = false;
#pragma unroll
  for (int r = 0; r < NR; r++) {
    float v0 = fmaxf(s[2 * r], s[2 * r + 1]), v1 = fmaxf(s[2 * r + 4], s[2 * r + 5]);
#pragma unroll
    for (int g = 2; g < 8; g += 2) {
      v0 = fmaxf(v0, fmaxf(s[2 * r + 4 * g], s[2 * r + 4 * g + 1]));
      v1 = fmaxf(v1, fmaxf(s[2 * r + 4 * g + 4], s[2 * r + 4 * g + 5]));
    }
    mx[r] = fmaxf(v0, v1) * c;
    need |= !(mx[r] - mc[2 * BLK + r] <= 8.f);
    alpha[r] = 1.f;
  }
  if (__any_sync(0xffffffffu, need)) {
#pragma unroll
    for (int r = 0; r < NR; r++) mx[r] = fmaxf(mx[r], __shfl_xor_sync(0xffffffffu, mx[r], 1));
#pragma unroll
    for (int r = 0; r < NR; r++) mx[r] = fmaxf(mx[r], __shfl_xor_sync(0xffffffffu, mx[r], 2));
#pragma unroll
    for (int r = 0; r < NR; r++) {
      const float mo = mc[2 * BLK + r];
      const float mn = fmaxf(mo, mx[r]);
      alpha[r] = ex2(mo - mn);
      mc[2 * BLK + r] = mn;
      l[2 * BLK + r] *= alpha[r];
    }
    flag = 1;
  }
#pragma unroll
  for (int r = 0; r < NR; r++) {
    const float nm = -mc[2 * BLK + r];
    float sum0 = l[2 * BLK + r], sum1 = 0.f;
#pragma unroll
    for (int g = 0; g < 8; g++) {
      const float p0 = ex2(fmaf(s[2 * r + 4 * g], c, nm));
      const float p1 = ex2(fmaf(s[2 * r + 4 * g + 1], c, nm));
      s[2 * r + 4 * g] = p0;
      s[2 * r + 4 * g + 1] = p1;
      sum0 += p0;
      sum1 += p1;
    }
    float lr = sum0 + sum1;
    if (LAST) {
      lr += __shfl_xor_sync(0xffffffffu, lr, 1);
      lr += __shfl_xor_sync(0xffffffffu, lr, 2);
      float inv;
      asm("rcp.approx.ftz.f32 %0, %1;" : "=f"(inv) : "f"(lr));
      alpha[r] *= inv;
#pragma unroll
      for (int g = 0; g < 8; g++) {
        s[2 * r + 4 * g] *= inv;
        s[2 * r + 4 * g + 1] *= inv;
      }
    }
    l[2 * BLK + r] = lr;
    if (!LAST) alpha[r] = fmaf(lr, 0.f, alpha[r]);
  }
  if (BLK < 2) {
    static_for<0, 4>([&](auto G) {
      constexpr int g = decltype(G)::value;
      const float* q = s + g * 8;
      stsm4_o<(g << 5), PB * QCHUNK + BLK * 8192>(cx.pa01, pack_bf16(q[0], q[1]), pack_bf16(q[2], q[3]), pack_bf16(q[4], q[5]),
                                    pack_bf16(q[6], q[7]));
    });
    if (cx.wr) {
      sts32(cx.sa01 + PB * 640 + BLK * 64, alpha[0]);
      sts32(cx.sa01 + PB * 640 + BLK * 64 + 8, alpha[NR - 1]);
    }
  } else {
    static_for<0, 2>([&](auto G) {
      constexpr int g = decltype(G)::value;
      const float* q = s + g * 16;
      stsm4_o<(g << 6), PB * QCHUNK>(cx.pa2, pack_bf16(q[0], q[1]), pack_bf16(q[4], q[5]), pack_bf16(q[8], q[9]),
                           pack_bf16(q[12], q[13]));
    });
    if (cx.wr) sts32(cx.sa2 + PB * 640, alpha[0]);
  }
}

template <int PB, bool LAST>
__device__ __forceinline__ void s_tile(int j, float* sX, float* sY, float* mc, float* l, const SCtx& cx, uint32_t& slot,
                                       int wi, int lane) {
  constexpr uint32_t sb = SB;
  uint32_t flag = LAST ? 1u : 0u;
  if (wi == 0) PROF(8 + j);
  PS(40);
  uint32_t dk = dlo(sb + OFF_SLOT) + slot * (SLOT_B >> 4);
  qk_issue<1>(sY, dk);
  PS(41);
  if (j >= 2) nb_sync(NB_PEMPTY + PB, 384);
  if (j >= 1) nb_arrive(NB_GO, 256);
  wg_wait<1>();
  reg_fence<32>(sX);
  PS(43);
  softmax_blk<0, PB, LAST>(sX, mc, l, flag, cx);
  PS(44);
  qk_issue<2>(sX, dk);
  if (j >= 1) nb_arrive(NB_GO + 1, 256);
  PS(45);
  wg_wait<1>();
  reg_fence<32>(sY);
  softmax_blk<1, PB, LAST>(sY, mc, l, flag, cx);
  PS(46);
  wg_wait<0>();
  reg_fence<32>(sX);
  if (lane == 0) mbar_arrive_n(sb + BAR_EMPTY + 8 * slot, 2);
  if (!LAST) {
    uint32_t use;
    kv_slot(2 * j + 1, slot, use);
    mbar_wait(sb + BAR_FULL + 8 * slot, use & 1);
    PS(47);
    dk = dlo(sb + OFF_SLOT) + slot * (SLOT_B >> 4);
    qk_issue<0>(sY, dk);
  }
  PS(48);
  softmax_blk<2, PB, LAST>(sX, mc, l, flag, cx);
  if (lane == 0) asm volatile("st.shared.u32 [%0], %1;" ::"r"(sb + OFF_FLAG + PB * 16 + wi * 4), "r"(flag) : "memory");
  PS(49);
  fence_async();
  nb_arrive(NB_PFULL + PB, 384);
  PS(50);
}

template <int NP>
__device__ __forceinline__ void reduce_panels(int p, uint32_t t, uint32_t bid, uint32_t parity, __nv_bfloat16* out) {
  const int blk = bid >> 6, kvh = (bid >> 3) & 7, b = bid & 7;
  const int e = 80 * kvh + t, el = e & 31;
  const uint4* gp = g_part + (size_t)(blk * 8 + b) * (8 * 7 * 640) + p * 640 + e;
  __nv_bfloat16* o = out + (size_t)(b * 80 + 16 * (e >> 7) + 2 * (el & 3)) * 896 + blk * 448 + 16 * ((e >> 5) & 3) +
                     (el >> 2) + p * 64;
  uint4 v[NP][8];
  uint32_t it = 0;
  while (true) {
    uint32_t bad = 0;
#pragma unroll
    for (int n = 0; n < NP; n++)
#pragma unroll
      for (int k = 0; k < 8; k++) v[n][k] = ld_relaxed128(gp + n * 640 + k * (7 * 640));
#pragma unroll
    for (int n = 0; n < NP; n++)
#pragma unroll
      for (int k = 0; k < 8; k++) bad |= v[n][k].x ^ parity;
    if (!(bad & 1u)) break;
    if (++it > (1u << 20)) __trap();
    __nanosleep(POLL_NS);
  }
#pragma unroll
  for (int n = 0; n < NP; n++) {
    float a[8];
#pragma unroll
    for (int i = 0; i < 8; i++) a[i] = 0.f;
#pragma unroll
    for (int k = 0; k < 8; k++) {
      a[0] += bf_lo(v[n][k].x); a[1] += bf_hi(v[n][k].x);
      a[2] += bf_lo(v[n][k].y); a[3] += bf_hi(v[n][k].y);
      a[4] += bf_lo(v[n][k].z); a[5] += bf_hi(v[n][k].z);
      a[6] += bf_lo(v[n][k].w); a[7] += bf_hi(v[n][k].w);
    }
#pragma unroll
    for (int i = 0; i < 8; i++) o[n * 64 + ((i & 1) + 8 * (i >> 2)) * 896 + 8 * ((i >> 1) & 1)] = __float2bfloat16(a[i]);
  }
}

__global__ void __launch_bounds__(NTHREADS, 1)
fused_gqa_kernel(const __grid_constant__ Maps maps, __nv_bfloat16* __restrict__ out, int ntile2) {
  extern __shared__ uint8_t smem_raw[];
  constexpr uint32_t sb = SB;
  if ((uint32_t)__cvta_generic_to_shared(smem_raw) != sb) __trap();
  const int wg = __shfl_sync(0xffffffffu, threadIdx.x >> 7, 0);
#define ROLE_IDS()                                                   \
  int tid, bid;                                                      \
  asm volatile("mov.u32 %0, %%tid.x;" : "=r"(tid));                  \
  asm volatile("mov.u32 %0, %%ctaid.x;" : "=r"(bid));                \
  const int wi = __shfl_sync(0xffffffffu, (tid >> 5) & 3, 0);        \
  const int lane = tid & 31;                                         \
  const int blk = bid >> 6, kvh = (bid >> 3) & 7, b = bid & 7;       \
  (void)wi; (void)lane; (void)blk; (void)kvh; (void)b

  if (threadIdx.x == 0) {
    const int blk = blockIdx.x >> 6, kvh = (blockIdx.x >> 3) & 7, b = blockIdx.x & 7;
    PROF(0);
    for (int s = 0; s < 4; s++) {
      mbar_init(sb + BAR_FULL + 8 * s, 1);
      mbar_init(sb + BAR_EMPTY + 8 * s, 8);
      mbar_init(sb + BAR_WFULL + 8 * s, 1);
      mbar_init(sb + BAR_WEMPT + 8 * s, 8);
    }
    mbar_init(sb + BAR_X, 1);
    mbar_init(sb + BAR_T, 1);
    for (int p = 0; p < 7; p++) mbar_init(sb + BAR_PW + 8 * p, 4);
    asm volatile("fence.mbarrier_init.release.cluster;" ::: "memory");
    fence_async();
    const CUtensorMap* mx = &maps.m[blk * 5 + 0];
    const CUtensorMap* mwq = &maps.m[blk * 5 + 3];
    mbar_expect_tx(sb + BAR_WFULL, WST_B);
    tma3d(sb + OFF_W, mwq, 0, kvh * 8, sb + BAR_WFULL);
    mbar_expect_tx(sb + BAR_X, 71680);
    tma3d(sb + OFF_Q, mx, b * 80, 0, sb + BAR_X);
    for (int t = 1; t < 4; t++) {
      mbar_expect_tx(sb + BAR_WFULL + 8 * t, WST_B);
      tma3d(sb + OFF_W + t * WST_B, mwq, 16 * t, kvh * 8, sb + BAR_WFULL + 8 * t);
    }
  }
  __syncthreads();

  if (wg == 0) {
    asm volatile("setmaxnreg.dec.sync.aligned.u32 24;");
    ROLE_IDS();
    if (tid == 32) {
      const uint32_t parity = ((atomicAdd(&g_ticket, 1u) >> 7) & 1u) ^ 1u;
      asm volatile("st.shared.u32 [%0], %1;" ::"r"(sb + OFF_MISC), "r"(parity) : "memory");
      mbar_arrive(sb + BAR_T);
    }
    if (tid == 0) {
      const CUtensorMap* mk = &maps.m[blk * 5 + 1];
      const CUtensorMap* mv = &maps.m[blk * 5 + 2];
      const CUtensorMap* mwq = &maps.m[blk * 5 + 3];
      const CUtensorMap* mwo = &maps.m[blk * 5 + 4];
      const int row0 = (b * 8 + kvh) * 1024;
      uint64_t pol;
      asm volatile("createpolicy.fractional.L2::" KV_POL ".b64 %0, 1.0;" : "=l"(pol));
#pragma unroll 1
      for (int t = 0; t < 3; t++) tma3d_pf(mwq, 16 * (4 + b + 8 * t), kvh * 8);
#pragma unroll 1
      for (int t = 4; t < 28; t++) {
        if (t >= K0_AT && ((t - K0_AT) % K_STEP) == 0 && (t - K0_AT) / K_STEP < 8) {
          const int q = (t - K0_AT) / K_STEP, i = q >> 2;
          if ((q & 3) == 0) mbar_expect_tx(sb + BAR_FULL + 8 * i, SLOT_B);
          tma3d_ef(sb + OFF_SLOT + q * 8192, &maps.k8[blk], row0 + 64 * i, q & 3, sb + BAR_FULL + 8 * i, pol);
        }
        const uint32_t s = t & 3;
        mbar_wait(sb + BAR_WEMPT + 8 * s, ((t >> 2) - 1) & 1);
        mbar_expect_tx(sb + BAR_WFULL + 8 * s, WST_B);
        tma3d(sb + OFF_W + s * WST_B, mwq, 16 * t, kvh * 8, sb + BAR_WFULL + 8 * s);
      }
      mbar_wait(sb + BAR_WEMPT, 0);
      mbar_wait(sb + BAR_WEMPT + 8, 0);
#pragma unroll 1
      for (int i = 2; i < 32; i++) {
        uint32_t s, use;
        kv_slot(i, s, use);
        const bool isv = !(i & 1) || (i == 31);
        const int j = (i == 31) ? 15 : (isv ? ((i - 2) >> 1) : ((i + 1) >> 1));
        if (use > 0) mbar_wait(sb + BAR_EMPTY + 8 * s, (use - 1) & 1);
        mbar_expect_tx(sb + BAR_FULL + 8 * s, SLOT_B);
        tma3d_ef(sb + OFF_SLOT + s * SLOT_B, isv ? mv : mk, row0 + 64 * j, 0, sb + BAR_FULL + 8 * s, pol);
        if (i == WO_AT) {
          tma3d_pf(mwo, kvh * 512 + 256 * (b & 1), b >> 1);
          if (b < 6) tma3d_pf(mwo, kvh * 512 + 256 * (b & 1), 4 + (b >> 1));
        }
      }
#pragma unroll 1
      for (int u = 0; u < 14; u++) {
        uint32_t s, use;
        wo_slot(u, s, use);
        if (use > 0) mbar_wait(sb + BAR_EMPTY + 8 * s, (use - 1) & 1);
        mbar_expect_tx(sb + BAR_FULL + 8 * s, SLOT_B);
        tma3d(sb + OFF_SLOT + s * SLOT_B, mwo, kvh * 512 + 256 * (u & 1), u >> 1, sb + BAR_FULL + 8 * s);
      }
    }
  } else if (wg == 1) {
    asm volatile(SREG_STR);
    ROLE_IDS();
    float m[5], l[5];
#pragma unroll
    for (int r = 0; r < 5; r++) { m[r] = -INFINITY; l[r] = 0.f; }
    SCtx cx;
    {
      const uint32_t li = lane & 7, lm = lane >> 3;
      cx.pa01 = sb + OFF_P + (16 * wi + li + 8 * (lm & 1)) * 128 + (((lm >> 1) ^ li) << 4);
      cx.pa2 = sb + OFF_P + (128 + 8 * wi + li) * 128 + ((lm ^ li) << 4);
      const uint32_t r8 = lane >> 2;
      cx.sa01 = sb + OFF_SC + (40 * (r8 >> 1) + 2 * (2 * wi) + (r8 & 1)) * 4;
      cx.sa2 = sb + OFF_SC + (40 * (r8 >> 1) + 2 * (16 + wi) + (r8 & 1)) * 4;
      cx.wr = (lane & 3) == 0;
    }
    nb_sync(NB_Q, 384);
    if (tid == 128) PROF(3);
    {
      float sA[32], sB[32];
      uint32_t slot = 0;
      mbar_wait(sb + BAR_FULL, 0);
      qk_issue<0>(sA, dlo(sb + OFF_SLOT));
      int j = 0;
#pragma unroll 1
      for (; j < ntile2; j += 2) {
        s_tile<0, false>(j, sA, sB, m, l, cx, slot, wi, lane);
        s_tile<1, false>(j + 1, sB, sA, m, l, cx, slot, wi, lane);
      }
      s_tile<0, false>(j, sA, sB, m, l, cx, slot, wi, lane);
      s_tile<1, true>(j + 1, sB, sA, m, l, cx, slot, wi, lane);
    }
    uint32_t tid2, bid2;
    asm volatile("mov.u32 %0, %%tid.x;" : "=r"(tid2));
    asm volatile("mov.u32 %0, %%ctaid.x;" : "=r"(bid2));
    if (!NO_RED && tid2 - 128 < 80) {
      uint32_t parity;
      mbar_wait(sb + BAR_T, 0);
      asm volatile("ld.shared.u32 %0, [%1];" : "=r"(parity) : "r"(sb + OFF_MISC) : "memory");
      mbar_wait(sb + BAR_PW + 8 * 2, 0);
      reduce_panels<2>(0, tid2 - 128, bid2, parity, out);
      if (tid2 == 128) PT(54);
      mbar_wait(sb + BAR_PW + 8 * 4, 0);
      reduce_panels<2>(2, tid2 - 128, bid2, parity, out);
      if (tid2 == 128) PT(56);
    }
    if (tid2 == 128) PROF(7);
  } else if (WITH_O) {
    asm volatile("setmaxnreg.inc.sync.aligned.u32 192;");
    ROLE_IDS();
    const int w = __shfl_sync(0xffffffffu, (tid >> 7) & 1, 0);
    const uint32_t li = lane & 7, lm = lane >> 3;
    {
      float acc[160];
#pragma unroll
      for (int i = 0; i < 160; i++) acc[i] = 0.f;
      reg_fence<160>(acc);
      mbar_wait(sb + BAR_X, 0);
      if (tid == 256) PROF(1);
#pragma unroll 1
      for (int t = 0; t < 28; t++) {
        const uint32_t st = t & 3;
        mbar_wait(sb + BAR_WFULL + 8 * st, (t >> 2) & 1);
        const uint32_t da = dlo(sb + OFF_W) + st * (WST_B >> 4) + w * (8192 >> 4);
        const uint32_t db = dlo(sb + OFF_Q) + (((t >> 2) * 10240 + (t & 3) * 32) >> 4);
        wg_fence();
        static_for<0, 4>([&](auto C) { constexpr int cc = decltype(C)::value; wgmma_n80_mk1<cc * 2048, 0>(acc + 40 * cc, da, db); });
        wg_commit();
        wg_wait<1>();
        if (t > 0 && lane == 0) mbar_arrive(sb + BAR_WEMPT + 8 * ((t - 1) & 3));
      }
      wg_wait<0>();
      reg_fence<160>(acc);
      nb_sync(NB_O, 256);
      if (tid == 256) PROF(2);
      const uint32_t qa = sb + OFF_Q + (80 * w + 8 * (lm >> 1) + li) * 128 + (((2 * wi + (lm & 1)) ^ li) << 4);
#pragma unroll
      for (int cc = 0; cc < 4; cc++)
#pragma unroll
        for (int jj = 0; jj < 5; jj++) {
          const float* q = acc + 40 * cc + 8 * jj;
          stsm4t(qa + cc * QCHUNK + jj * 2048, pack_bf16(q[0], q[1]), pack_bf16(q[2], q[3]), pack_bf16(q[4], q[5]),
                 pack_bf16(q[6], q[7]));
        }
      fence_async();
      nb_arrive(NB_Q, 384);
    }
    {
    float acc[160];
#pragma unroll
    for (int i = 0; i < 160; i++) acc[i] = 0.f;
    reg_fence<160>(acc);
#pragma unroll 1
    for (int j = 0; j < 16; j++) {
      const uint32_t pb = j & 1;
      PO(52);
      nb_sync(NB_PFULL + pb, 384);
      PO(53);
      if (j > 0) {
        const float4 f = lds128(sb + OFF_FLAG + pb * 16);
        if ((__float_as_uint(f.x) | __float_as_uint(f.y) | __float_as_uint(f.z) | __float_as_uint(f.w)) != 0) {
          const uint32_t sc = sb + OFF_SC + pb * 640 + (lane & 3) * 160;
#pragma unroll
          for (int g = 0; g < 10; g++) {
            const float4 a = lds128(sc + g * 16);
#pragma unroll
            for (int mb = 0; mb < 2; mb++) {
              float* q = acc + 80 * mb + 8 * g;
              q[0] *= a.x; q[1] *= a.y; q[2] *= a.x; q[3] *= a.y;
              q[4] *= a.z; q[5] *= a.w; q[6] *= a.z; q[7] *= a.w;
            }
          }
        }
      }
      uint32_t slot, use;
      kv_slot(j == 15 ? 31 : 2 * j + 2, slot, use);
      reg_fence<160>(acc);
      PO(54);
      if (j < 15) nb_sync(NB_GO + w, 256);
      mbar_wait(sb + BAR_FULL + 8 * slot, use & 1);
      if (tid == 256) PROF(24 + j);
      PO(55);
      const uint32_t da = dlo(sb + OFF_SLOT) + slot * (SLOT_B >> 4) + w * (16384 >> 4);
      const uint32_t db = dlo(sb + OFF_P) + pb * (QCHUNK >> 4);
      wg_fence();
      static_for<0, 4>([&](auto K) {
        constexpr int ks = decltype(K)::value;
        wgmma_n160_mk1<ks * 2048, ks * 32>(acc, da, db);
        wgmma_n160_mk1<8192 + ks * 2048, ks * 32>(acc + 80, da, db);
      });
      wg_commit();
      PO(56);
      wg_wait<0>();
      reg_fence<160>(acc);
      PO(57);
      if (lane == 0) mbar_arrive(sb + BAR_EMPTY + 8 * slot);
      if (j < 14) nb_arrive(NB_PEMPTY + pb, 384);
    }
    if (tid == 256) PROF(4);
    {
      const uint32_t oa = sb + OFF_Q + 2 * w * QCHUNK + (8 * (lm >> 1) + li) * 128 + (((2 * wi + (lm & 1)) ^ li) << 4);
#pragma unroll
      for (int mb = 0; mb < 2; mb++)
#pragma unroll
        for (int jj = 0; jj < 10; jj++) {
          const float* q = acc + 80 * mb + 8 * jj;
          stsm4t(oa + mb * QCHUNK + jj * 2048, pack_bf16(q[0], q[1]), pack_bf16(q[2], q[3]), pack_bf16(q[4], q[5]),
                 pack_bf16(q[6], q[7]));
        }
      fence_async();
      nb_sync(NB_O, 256);
    }
    }
    if (tid == 256) PROF(5);
    uint32_t parity;
    mbar_wait(sb + BAR_T, 0);
    asm volatile("ld.shared.u32 %0, [%1];" : "=r"(parity) : "r"(sb + OFF_MISC) : "memory");
    uint32_t tid2, bid2;
    asm volatile("mov.u32 %0, %%tid.x;" : "=r"(tid2));
    asm volatile("mov.u32 %0, %%ctaid.x;" : "=r"(bid2));
    uint4* gp = g_part + ((size_t)((bid2 >> 6) * 8 + (bid2 & 7)) * 8 + ((bid2 >> 3) & 7)) * (7 * 640) + (tid2 & 127);
    constexpr uint32_t dob = dlo(sb + OFF_Q);
#pragma unroll 1
    for (int p = w; p < 7; p += 2) {
      float acc[40];
      uint32_t slot0, use0, slot1, use1;
      wo_slot(2 * p, slot0, use0);
      wo_slot(2 * p + 1, slot1, use1);
      mbar_wait(sb + BAR_FULL + 8 * slot0, use0 & 1);
      if (p > 0) nb_sync(NB_ORD + w, 256);
      if ((tid2 & 127) == 0) PT(40 + p);
      uint32_t da = dlo(sb + OFF_SLOT) + slot0 * (SLOT_B >> 4);
      wg_fence();
      wgmma_n80_mk_z<0, 0>(acc, da, dob);
      static_for<1, 16>([&](auto K) {
        constexpr int ks = decltype(K)::value;
        wgmma_n80_mk1<ks * 2048, (ks >> 2) * QCHUNK + (ks & 3) * 32>(acc, da, dob);
      });
      wg_commit();
      mbar_wait(sb + BAR_FULL + 8 * slot1, use1 & 1);
      da = dlo(sb + OFF_SLOT) + slot1 * (SLOT_B >> 4);
      wg_fence();
      static_for<0, 6>([&](auto K) {
        constexpr int ks = decltype(K)::value;
        wgmma_n80_mk1<ks * 2048, 10240 + (ks >> 2) * QCHUNK + (ks & 3) * 32>(acc, da, dob);
      });
      wg_commit();
      wg_wait<1>();
      if (lane == 0) mbar_arrive_n(sb + BAR_EMPTY + 8 * slot0, 2);
      wg_fence();
      static_for<6, 16>([&](auto K) {
        constexpr int ks = decltype(K)::value;
        wgmma_n80_mk1<ks * 2048, 10240 + (ks >> 2) * QCHUNK + (ks & 3) * 32>(acc, da, dob);
      });
      wg_commit();
      if (p < 6) nb_arrive(NB_ORD + (w ^ 1), 256);
      wg_wait<0>();
      reg_fence<40>(acc);
      if (lane == 0) mbar_arrive_n(sb + BAR_EMPTY + 8 * slot1, 2);
#pragma unroll
      for (int k = 0; k < 5; k++) {
        const float* q = acc + 8 * k;
        const uint32_t w0 = pack_bf16(q[0], q[1]), w1 = pack_bf16(q[2], q[3]);
        const uint32_t w2 = pack_bf16(q[4], q[5]), w3 = pack_bf16(q[6], q[7]);
        if (!NO_ST || w0 == 0x12345678u) st_relaxed128(gp + p * 640 + k * 128, (w0 & ~1u) | parity, w1, w2, w3);
      }
      __syncwarp();
      if (lane == 0) mbar_arrive(sb + BAR_PW + 8 * p);
      if ((tid2 & 127) == 0) PT(47 + p);
    }
    if (tid == 256) PROF(6);
    if (!NO_RED && (tid2 & 127) < 80) {
      if (w == 1) reduce_panels<2>(4, tid2 & 127, bid2, parity, out);
      else reduce_panels<1>(6, tid2 & 127, bid2, parity, out);
    }
    if ((tid2 & 127) == 0) PT(58 + 2 * (1 - w));
  }
}

typedef CUresult (*EncodeFn)(CUtensorMap*, CUtensorMapDataType, cuuint32_t, void*, const cuuint64_t*, const cuuint64_t*,
                             const cuuint32_t*, const cuuint32_t*, CUtensorMapInterleave, CUtensorMapSwizzle,
                             CUtensorMapL2promotion, CUtensorMapFloatOOBfill);

void encode3d(EncodeFn enc, CUtensorMap* m, void* p, uint64_t rows, uint64_t cols, uint32_t box_rows,
              uint32_t box_blocks) {
  cuuint64_t dims[3] = {64, rows, cols / 64};
  cuuint64_t strides[2] = {cols * 2, 128};
  cuuint32_t box[3] = {64, box_rows, box_blocks};
  cuuint32_t es[3] = {1, 1, 1};
  enc(m, CU_TENSOR_MAP_DATA_TYPE_BFLOAT16, 3, p, dims, strides, box, es, CU_TENSOR_MAP_INTERLEAVE_NONE,
      CU_TENSOR_MAP_SWIZZLE_128B, CU_TENSOR_MAP_L2_PROMOTION_L2_256B, CU_TENSOR_MAP_FLOAT_OOB_FILL_NONE);
}

}

extern "C" void kernel_launch(void* const* d_in, const int* in_sizes, int n_in, void* d_out, int out_size) {
  static EncodeFn enc = nullptr;
  if (!enc) {
    void* fn = nullptr;
    cudaDriverEntryPointQueryResult qr;
    cudaGetDriverEntryPoint("cuTensorMapEncodeTiled", &fn, cudaEnableDefault, &qr);
    enc = (EncodeFn)fn;
    cudaFuncSetAttribute(fused_gqa_kernel, cudaFuncAttributeMaxDynamicSharedMemorySize, SMEM_BYTES);
  }
  Maps maps;
  for (int blk = 0; blk < 2; blk++) {
    encode3d(enc, &maps.m[blk * 5 + 0], d_in[blk * 5 + 0], 640, 448, 80, 7);
    encode3d(enc, &maps.m[blk * 5 + 1], d_in[blk * 5 + 1], 65536, 256, 64, 4);
    encode3d(enc, &maps.m[blk * 5 + 2], d_in[blk * 5 + 2], 65536, 256, 64, 4);
    encode3d(enc, &maps.m[blk * 5 + 3], d_in[blk * 5 + 3], 448, 4096, 16, 8);
    encode3d(enc, &maps.m[blk * 5 + 4], d_in[blk * 5 + 4], 4096, 448, 256, 1);
    encode3d(enc, &maps.k8[blk], d_in[blk * 5 + 1], 65536, 256, 64, 1);
  }
  fused_gqa_kernel<<<NCTA, NTHREADS, SMEM_BYTES>>>(maps, (__nv_bfloat16*)d_out, 14);
}
```

```cpp
#include <cuda_runtime.h>
#include <cuda_bf16.h>
#include <cuda.h>
#include <stdint.h>

namespace {

constexpr int NCTA = 128;
constexpr int NTHREADS = 512;

constexpr uint32_t SB = 0x400;
constexpr uint32_t OFF_Q     = 0;
constexpr uint32_t QCHUNK    = 20480;
constexpr uint32_t OFF_SLOT  = 81920;
constexpr uint32_t SLOT_B    = 32768;
constexpr uint32_t OFF_P     = OFF_SLOT + 3 * SLOT_B;
constexpr uint32_t OFF_W     = OFF_SLOT + SLOT_B;
constexpr uint32_t WST_B     = 16384;
constexpr uint32_t OFF_SC    = OFF_P + 2 * QCHUNK;
constexpr uint32_t OFF_FLAG  = OFF_SC + 1280;
constexpr uint32_t OFF_LINV  = OFF_FLAG + 32;
constexpr uint32_t OFF_ST    = OFF_P + SLOT_B;
constexpr uint32_t OFF_BAR   = OFF_ST + 18432;
constexpr uint32_t BAR_FULL  = OFF_BAR;
constexpr uint32_t BAR_EMPTY = BAR_FULL + 32;
constexpr uint32_t BAR_WFULL = BAR_EMPTY + 32;
constexpr uint32_t BAR_WEMPT = BAR_WFULL + 48;
constexpr uint32_t BAR_T     = BAR_WEMPT + 48;
constexpr uint32_t OFF_MISC  = BAR_T + 8;
constexpr uint32_t OFF_PROF  = OFF_MISC + 16;
constexpr uint32_t SMEM_USED = OFF_PROF + 256;
constexpr uint32_t SMEM_BYTES = SMEM_USED;

#define SREG_STR "setmaxnreg.dec.sync.aligned.u32 104;"
#define WITH_O 1
#define PACE_TAU 1340
#define PACE_T0 3400
#define POLL_NS 100
#define S_AFTER 5
#define X_OFF 1
#define WPF_0 8
#define WPF_A 6
#define WPF_B 9
#define WPF_C 12
#define WAIT_HINT ""
#define SWAP 0
#define PACE_END 32
#define NPRE 6
#define TEST_KS 9
#define QTEST 1
#define LAST_ORD 1
#define EXP 0
#define ZERO_NS 20000
#define K0_AT 16
#define K_STEP 2
#define WO_AT 99
#define KV_POL "evict_first"

struct Maps {
  CUtensorMap m[10];
  CUtensorMap k8[2];
  CUtensorMap o;
};

__device__ unsigned int g_zero[16 * 32];
__device__ unsigned int g_ticket;
#define PT(idx) do {} while (0)
#define PS(idx) do {} while (0)
#define PO(idx) do {} while (0)
#define PROF(idx) do {} while (0)

__device__ __forceinline__ void mbar_init(uint32_t bar, uint32_t cnt) {
  asm volatile("mbarrier.init.shared::cta.b64 [%0], %1;" ::"r"(bar), "r"(cnt) : "memory");
}
__device__ __forceinline__ void mbar_expect_tx(uint32_t bar, uint32_t bytes) {
  asm volatile("mbarrier.arrive.expect_tx.shared::cta.b64 _, [%0], %1;" ::"r"(bar), "r"(bytes) : "memory");
}
__device__ __forceinline__ void mbar_arrive(uint32_t bar) {
  asm volatile("mbarrier.arrive.shared::cta.b64 _, [%0];" ::"r"(bar) : "memory");
}
__device__ __forceinline__ void mbar_arrive_n(uint32_t bar, uint32_t n) {
  asm volatile("mbarrier.arrive.shared::cta.b64 _, [%0], %1;" ::"r"(bar), "r"(n) : "memory");
}
__device__ __forceinline__ void mbar_wait(uint32_t bar, uint32_t parity) {
  asm volatile(
      "{\n.reg .pred p;\n.reg .u32 c;\nmov.u32 c, 0;\n"
      "W_LOOP:\n"
      "mbarrier.try_wait.parity.shared::cta.b64 p, [%0], %1" WAIT_HINT ";\n"
      "@p bra W_DONE;\n"
      "add.u32 c, c, 1;\n"
      "setp.lt.u32 p, c, 0x400000;\n"
      "@p bra W_LOOP;\n"
      "trap;\n"
      "W_DONE:\n}\n" ::"r"(bar), "r"(parity) : "memory");
}
__device__ __forceinline__ uint32_t mbar_test(uint32_t bar, uint32_t parity) {
  uint32_t ok;
  asm volatile("{\n.reg .pred p;\nmbarrier.test_wait.parity.shared::cta.b64 p, [%1], %2;\nselp.u32 %0, 1, 0, p;\n}\n"
               : "=r"(ok) : "r"(bar), "r"(parity) : "memory");
  return ok;
}
__device__ __forceinline__ void nb_sync(uint32_t id, uint32_t n) { asm volatile("bar.sync %0, %1;" ::"r"(id), "r"(n) : "memory"); }
__device__ __forceinline__ void nb_arrive(uint32_t id, uint32_t n) { asm volatile("bar.arrive %0, %1;" ::"r"(id), "r"(n) : "memory"); }
constexpr uint32_t NB_O = 1, NB_PFULL = 2, NB_PEMPTY = 4, NB_GO = 6, NB_Q = 8, NB_ORD = 10, NB_O2 = 12, NB_S = 13, NB_SF = 14;
__device__ __forceinline__ uint32_t nb_se(uint32_t w) { return w ? NB_S : NB_Q; }
__device__ __forceinline__ void tma3d(uint32_t dst, const CUtensorMap* m, int c1, int c2, uint32_t bar) {
  asm volatile(
      "cp.async.bulk.tensor.3d.shared::cluster.global.mbarrier::complete_tx::bytes [%0], [%1, {%2, %3, %4}], [%5];"
      ::"r"(dst), "l"(m), "r"(0), "r"(c1), "r"(c2), "r"(bar) : "memory");
}
__device__ __forceinline__ void tma3d_ef(uint32_t dst, const CUtensorMap* m, int c1, int c2, uint32_t bar, uint64_t pol) {
  asm volatile(
      "cp.async.bulk.tensor.3d.shared::cluster.global.mbarrier::complete_tx::bytes.L2::cache_hint [%0], [%1, {%2, %3, %4}], [%5], %6;"
      ::"r"(dst), "l"(m), "r"(0), "r"(c1), "r"(c2), "r"(bar), "l"(pol) : "memory");
}
__device__ __forceinline__ void tma3d_pf(const CUtensorMap* m, int c1, int c2) {
  asm volatile("cp.async.bulk.prefetch.tensor.3d.L2.global [%0, {%1, %2, %3}];" ::"l"(m), "r"(0), "r"(c1), "r"(c2)
               : "memory");
}
__device__ __forceinline__ void wg_fence() { asm volatile("wgmma.fence.sync.aligned;" ::: "memory"); }
__device__ __forceinline__ void wg_commit() { asm volatile("wgmma.commit_group.sync.aligned;" ::: "memory"); }
template <int N>
__device__ __forceinline__ void wg_wait() { asm volatile("wgmma.wait_group.sync.aligned %0;" ::"n"(N) : "memory"); }
__device__ __forceinline__ void fence_async() { asm volatile("fence.proxy.async.shared::cta;" ::: "memory"); }
template <int N>
__device__ __forceinline__ void reg_fence(float* d) {
#pragma unroll
  for (int i = 0; i < N; i++) asm volatile("" : "+f"(d[i])::"memory");
}
__device__ __forceinline__ constexpr uint32_t dlo(uint32_t saddr) { return ((saddr & 0x3FFFFu) >> 4) | (1u << 16); }
template <int V>
struct IC { static constexpr int value = V; };
template <int I, int N, class F>
__device__ __forceinline__ void static_for(F&& f) {
  if constexpr (I < N) {
    f(IC<I>{});
    static_for<I + 1, N>(f);
  }
}
__device__ __forceinline__ uint32_t pack_bf16(float lo, float hi) {
  uint32_t r;
  asm("cvt.rn.bf16x2.f32 %0, %1, %2;" : "=r"(r) : "f"(hi), "f"(lo));
  return r;
}
template <uint32_t XR, uint32_t OFF>
__device__ __forceinline__ void stsm4_o(uint32_t a, uint32_t r0, uint32_t r1, uint32_t r2, uint32_t r3) {
  asm volatile("{\n.reg .b32 t;\nxor.b32 t, %0, %6;\nstmatrix.sync.aligned.m8n8.x4.shared.b16 [t + %5], {%1, %2, %3, %4};\n}\n"
               ::"r"(a), "r"(r0), "r"(r1), "r"(r2), "r"(r3), "n"(OFF), "n"(XR) : "memory");
}
__device__ __forceinline__ void stsm4t(uint32_t a, uint32_t r0, uint32_t r1, uint32_t r2, uint32_t r3) {
  asm volatile("stmatrix.sync.aligned.m8n8.x4.trans.shared.b16 [%0], {%1, %2, %3, %4};" ::"r"(a), "r"(r0), "r"(r1),
               "r"(r2), "r"(r3) : "memory");
}
__device__ __forceinline__ float ex2(float x) {
  float y;
  asm("ex2.approx.ftz.f32 %0, %1;" : "=f"(y) : "f"(x));
  return y;
}
__device__ __forceinline__ float4 lds128(uint32_t a) {
  float4 v;
  asm volatile("ld.shared.v4.f32 {%0, %1, %2, %3}, [%4];" : "=f"(v.x), "=f"(v.y), "=f"(v.z), "=f"(v.w) : "r"(a) : "memory");
  return v;
}
__device__ __forceinline__ void sts32(uint32_t a, float v) {
  asm volatile("st.shared.f32 [%0], %1;" ::"r"(a), "f"(v) : "memory");
}
template <uint32_t OA, uint32_t OB, uint32_t HIA = 0x40000040u>
__device__ __forceinline__ void wgmma_n64_kk_z(float* d, uint32_t a, uint32_t b) {
  asm volatile(
      "{\n.reg .b32 ta, tb;\n.reg .b64 da, db;\nadd.u32 ta, %32, %34;\nadd.u32 tb, %33, %35;\nmov.b64 da, {ta, %36};\nmov.b64 db, {tb, 0x40000040};\n"
      "wgmma.mma_async.sync.aligned.m64n64k16.f32.bf16.bf16 {"
      "%0, %1, %2, %3, %4, %5, %6, %7, %8, %9, %10, %11, %12, %13, %14, %15,"
      "%16, %17, %18, %19, %20, %21, %22, %23, %24, %25, %26, %27, %28, %29, %30, %31}, da, db, 0, 1, 1, 0, 0;\n}\n"
      : "=f"(d[0]), "=f"(d[1]), "=f"(d[2]), "=f"(d[3]), "=f"(d[4]), "=f"(d[5]), "=f"(d[6]), "=f"(d[7]),
        "=f"(d[8]), "=f"(d[9]), "=f"(d[10]), "=f"(d[11]), "=f"(d[12]), "=f"(d[13]), "=f"(d[14]), "=f"(d[15]),
        "=f"(d[16]), "=f"(d[17]), "=f"(d[18]), "=f"(d[19]), "=f"(d[20]), "=f"(d[21]), "=f"(d[22]), "=f"(d[23]),
        "=f"(d[24]), "=f"(d[25]), "=f"(d[26]), "=f"(d[27]), "=f"(d[28]), "=f"(d[29]), "=f"(d[30]), "=f"(d[31])
      : "r"(a), "r"(b), "n"(OA >> 4), "n"(OB >> 4), "n"(HIA));
}

template <uint32_t OA, uint32_t OB, uint32_t HIA = 0x40000040u>
__device__ __forceinline__ void wgmma_n64_kk(float* d, uint32_t a, uint32_t b) {
  asm volatile(
      "{\n.reg .b32 ta, tb;\n.reg .b64 da, db;\nadd.u32 ta, %32, %34;\nadd.u32 tb, %33, %35;\nmov.b64 da, {ta, %36};\nmov.b64 db, {tb, 0x40000040};\n"
      "wgmma.mma_async.sync.aligned.m64n64k16.f32.bf16.bf16 {"
      "%0, %1, %2, %3, %4, %5, %6, %7, %8, %9, %10, %11, %12, %13, %14, %15,"
      "%16, %17, %18, %19, %20, %21, %22, %23, %24, %25, %26, %27, %28, %29, %30, %31}, da, db, 1, 1, 1, 0, 0;\n}\n"
      : "+f"(d[0]), "+f"(d[1]), "+f"(d[2]), "+f"(d[3]), "+f"(d[4]), "+f"(d[5]), "+f"(d[6]), "+f"(d[7]),
        "+f"(d[8]), "+f"(d[9]), "+f"(d[10]), "+f"(d[11]), "+f"(d[12]), "+f"(d[13]), "+f"(d[14]), "+f"(d[15]),
        "+f"(d[16]), "+f"(d[17]), "+f"(d[18]), "+f"(d[19]), "+f"(d[20]), "+f"(d[21]), "+f"(d[22]), "+f"(d[23]),
        "+f"(d[24]), "+f"(d[25]), "+f"(d[26]), "+f"(d[27]), "+f"(d[28]), "+f"(d[29]), "+f"(d[30]), "+f"(d[31])
      : "r"(a), "r"(b), "n"(OA >> 4), "n"(OB >> 4), "n"(HIA));
}

template <uint32_t OA, uint32_t OB, uint32_t HIA = 0x40000040u>
__device__ __forceinline__ void wgmma_n80_mk_z(float* d, uint32_t a, uint32_t b) {
  asm volatile(
      "{\n.reg .b32 ta, tb;\n.reg .b64 da, db;\nadd.u32 ta, %40, %42;\nadd.u32 tb, %41, %43;\nmov.b64 da, {ta, %44};\nmov.b64 db, {tb, 0x40000040};\n"
      "wgmma.mma_async.sync.aligned.m64n80k16.f32.bf16.bf16 {"
      "%0, %1, %2, %3, %4, %5, %6, %7, %8, %9, %10, %11, %12, %13, %14, %15,"
      "%16, %17, %18, %19, %20, %21, %22, %23, %24, %25, %26, %27, %28, %29, %30, %31,"
      "%32, %33, %34, %35, %36, %37, %38, %39}, da, db, 0, 1, 1, 1, 0;\n}\n"
      : "=f"(d[0]), "=f"(d[1]), "=f"(d[2]), "=f"(d[3]), "=f"(d[4]), "=f"(d[5]), "=f"(d[6]), "=f"(d[7]),
        "=f"(d[8]), "=f"(d[9]), "=f"(d[10]), "=f"(d[11]), "=f"(d[12]), "=f"(d[13]), "=f"(d[14]), "=f"(d[15]),
        "=f"(d[16]), "=f"(d[17]), "=f"(d[18]), "=f"(d[19]), "=f"(d[20]), "=f"(d[21]), "=f"(d[22]), "=f"(d[23]),
        "=f"(d[24]), "=f"(d[25]), "=f"(d[26]), "=f"(d[27]), "=f"(d[28]), "=f"(d[29]), "=f"(d[30]), "=f"(d[31]),
        "=f"(d[32]), "=f"(d[33]), "=f"(d[34]), "=f"(d[35]), "=f"(d[36]), "=f"(d[37]), "=f"(d[38]), "=f"(d[39])
      : "r"(a), "r"(b), "n"(OA >> 4), "n"(OB >> 4), "n"(HIA));
}

template <uint32_t OA, uint32_t OB, uint32_t HIA = 0x40000040u>
__device__ __forceinline__ void wgmma_n80_mk1(float* d, uint32_t a, uint32_t b) {
  asm volatile(
      "{\n.reg .b32 ta, tb;\n.reg .b64 da, db;\nadd.u32 ta, %40, %42;\nadd.u32 tb, %41, %43;\nmov.b64 da, {ta, %44};\nmov.b64 db, {tb, 0x40000040};\n"
      "wgmma.mma_async.sync.aligned.m64n80k16.f32.bf16.bf16 {"
      "%0, %1, %2, %3, %4, %5, %6, %7, %8, %9, %10, %11, %12, %13, %14, %15,"
      "%16, %17, %18, %19, %20, %21, %22, %23, %24, %25, %26, %27, %28, %29, %30, %31,"
      "%32, %33, %34, %35, %36, %37, %38, %39}, da, db, 1, 1, 1, 1, 0;\n}\n"
      : "+f"(d[0]), "+f"(d[1]), "+f"(d[2]), "+f"(d[3]), "+f"(d[4]), "+f"(d[5]), "+f"(d[6]), "+f"(d[7]),
        "+f"(d[8]), "+f"(d[9]), "+f"(d[10]), "+f"(d[11]), "+f"(d[12]), "+f"(d[13]), "+f"(d[14]), "+f"(d[15]),
        "+f"(d[16]), "+f"(d[17]), "+f"(d[18]), "+f"(d[19]), "+f"(d[20]), "+f"(d[21]), "+f"(d[22]), "+f"(d[23]),
        "+f"(d[24]), "+f"(d[25]), "+f"(d[26]), "+f"(d[27]), "+f"(d[28]), "+f"(d[29]), "+f"(d[30]), "+f"(d[31]),
        "+f"(d[32]), "+f"(d[33]), "+f"(d[34]), "+f"(d[35]), "+f"(d[36]), "+f"(d[37]), "+f"(d[38]), "+f"(d[39])
      : "r"(a), "r"(b), "n"(OA >> 4), "n"(OB >> 4), "n"(HIA));
}

template <uint32_t OA, uint32_t OB, uint32_t HIA = 0x40000040u>
__device__ __forceinline__ void wgmma_n160_mk1(float* d, uint32_t a, uint32_t b) {
  asm volatile(
      "{\n.reg .b32 ta, tb;\n.reg .b64 da, db;\nadd.u32 ta, %80, %82;\nadd.u32 tb, %81, %83;\nmov.b64 da, {ta, %84};\nmov.b64 db, {tb, 0x40000040};\n"
      "wgmma.mma_async.sync.aligned.m64n160k16.f32.bf16.bf16 {"
      "%0, %1, %2, %3, %4, %5, %6, %7, %8, %9, %10, %11, %12, %13, %14, %15,"
      "%16, %17, %18, %19, %20, %21, %22, %23, %24, %25, %26, %27, %28, %29, %30, %31,"
      "%32, %33, %34, %35, %36, %37, %38, %39, %40, %41, %42, %43, %44, %45, %46, %47,"
      "%48, %49, %50, %51, %52, %53, %54, %55, %56, %57, %58, %59, %60, %61, %62, %63,"
      "%64, %65, %66, %67, %68, %69, %70, %71, %72, %73, %74, %75, %76, %77, %78, %79}, da, db, 1, 1, 1, 1, 0;\n}\n"
      : "+f"(d[0]), "+f"(d[1]), "+f"(d[2]), "+f"(d[3]), "+f"(d[4]), "+f"(d[5]), "+f"(d[6]), "+f"(d[7]),
        "+f"(d[8]), "+f"(d[9]), "+f"(d[10]), "+f"(d[11]), "+f"(d[12]), "+f"(d[13]), "+f"(d[14]), "+f"(d[15]),
        "+f"(d[16]), "+f"(d[17]), "+f"(d[18]), "+f"(d[19]), "+f"(d[20]), "+f"(d[21]), "+f"(d[22]), "+f"(d[23]),
        "+f"(d[24]), "+f"(d[25]), "+f"(d[26]), "+f"(d[27]), "+f"(d[28]), "+f"(d[29]), "+f"(d[30]), "+f"(d[31]),
        "+f"(d[32]), "+f"(d[33]), "+f"(d[34]), "+f"(d[35]), "+f"(d[36]), "+f"(d[37]), "+f"(d[38]), "+f"(d[39]),
        "+f"(d[40]), "+f"(d[41]), "+f"(d[42]), "+f"(d[43]), "+f"(d[44]), "+f"(d[45]), "+f"(d[46]), "+f"(d[47]),
        "+f"(d[48]), "+f"(d[49]), "+f"(d[50]), "+f"(d[51]), "+f"(d[52]), "+f"(d[53]), "+f"(d[54]), "+f"(d[55]),
        "+f"(d[56]), "+f"(d[57]), "+f"(d[58]), "+f"(d[59]), "+f"(d[60]), "+f"(d[61]), "+f"(d[62]), "+f"(d[63]),
        "+f"(d[64]), "+f"(d[65]), "+f"(d[66]), "+f"(d[67]), "+f"(d[68]), "+f"(d[69]), "+f"(d[70]), "+f"(d[71]),
        "+f"(d[72]), "+f"(d[73]), "+f"(d[74]), "+f"(d[75]), "+f"(d[76]), "+f"(d[77]), "+f"(d[78]), "+f"(d[79])
      : "r"(a), "r"(b), "n"(OA >> 4), "n"(OB >> 4), "n"(HIA));
}

__device__ __forceinline__ void kv_slot(int i, uint32_t& slot, uint32_t& use) {
  use = (uint32_t)i / 3u;
  slot = (uint32_t)i - use * 3u;
}
__device__ __forceinline__ void wo_slot(int u, uint32_t& slot, uint32_t& use) {
  uint32_t r = u & 3, q = u >> 2;
  slot = (r == 0) ? 2u : (r == 3) ? 3u : (r - 1u);
  use = q + ((r == 0) ? 10u : (r == 3) ? 0u : 11u);
}

struct SCtx {
  uint32_t pa01, pa2, sa01, sa2;
  bool wr;
};

template <int BLK>
__device__ __forceinline__ void qk_issue(float* s, uint32_t dk) {
  constexpr uint32_t dq = dlo(SB + OFF_Q + BLK * 8192);
  constexpr uint32_t HI = (BLK == 2) ? 0x40000020u : 0x40000040u;
  wg_fence();
  constexpr uint32_t T = BLK << 20;
  wgmma_n64_kk_z<0, T, HI>(s, dq, dk);
  static_for<1, 16>([&](auto I) {
    constexpr int ks = decltype(I)::value;
    wgmma_n64_kk<(ks >> 2) * QCHUNK + (ks & 3) * 32, T + (ks >> 2) * 8192 + (ks & 3) * 32, HI>(s, dq, dk);
  });
  wg_commit();
}

template <int BLK, class F>
__device__ __forceinline__ void softmax_blk(float* s, float* mc, float* l, uint32_t& flag, const SCtx& cx, F&& mid) {
  constexpr int PB = 0;
  constexpr float c = 0.0625f * 1.4426950408889634f;
  constexpr int NR = (BLK == 2) ? 1 : 2;
  float mx[NR], alpha[NR];
  bool need = false;
#pragma unroll
  for (int r = 0; r < NR; r++) {
    float v0 = fmaxf(s[2 * r], s[2 * r + 1]), v1 = fmaxf(s[2 * r + 4], s[2 * r + 5]);
#pragma unroll
    for (int g = 2; g < 8; g += 2) {
      v0 = fmaxf(v0, fmaxf(s[2 * r + 4 * g], s[2 * r + 4 * g + 1]));
      v1 = fmaxf(v1, fmaxf(s[2 * r + 4 * g + 4], s[2 * r + 4 * g + 5]));
    }
    mx[r] = fmaxf(v0, v1) * c;
    need |= !(mx[r] - mc[2 * BLK + r] <= 8.f);
    alpha[r] = 1.f;
  }
  if (__any_sync(0xffffffffu, need)) {
#pragma unroll
    for (int r = 0; r < NR; r++) mx[r] = fmaxf(mx[r], __shfl_xor_sync(0xffffffffu, mx[r], 1));
#pragma unroll
    for (int r = 0; r < NR; r++) mx[r] = fmaxf(mx[r], __shfl_xor_sync(0xffffffffu, mx[r], 2));
#pragma unroll
    for (int r = 0; r < NR; r++) {
      const float mo = mc[2 * BLK + r];
      const float mn = fmaxf(mo, mx[r]);
      alpha[r] = ex2(mo - mn);
      mc[2 * BLK + r] = mn;
      l[2 * BLK + r] *= alpha[r];
    }
    flag = 1;
  }
#pragma unroll
  for (int r = 0; r < NR; r++) {
    const float nm = -mc[2 * BLK + r];
    float sum0 = l[2 * BLK + r], sum1 = 0.f;
#pragma unroll
    for (int g = 0; g < 8; g++) {
      const float p0 = ex2(fmaf(s[2 * r + 4 * g], c, nm));
      const float p1 = ex2(fmaf(s[2 * r + 4 * g + 1], c, nm));
      s[2 * r + 4 * g] = p0;
      s[2 * r + 4 * g + 1] = p1;
      sum0 += p0;
      sum1 += p1;
    }
    const float lr = sum0 + sum1;
    l[2 * BLK + r] = lr;
    alpha[r] = fmaf(lr, 0.f, alpha[r]);
    if (r == 0) mid();
  }
  if (BLK < 2) {
    static_for<0, 4>([&](auto G) {
      constexpr int g = decltype(G)::value;
      const float* q = s + g * 8;
      stsm4_o<(g << 5), PB * QCHUNK + BLK * 8192>(cx.pa01, pack_bf16(q[0], q[1]), pack_bf16(q[2], q[3]), pack_bf16(q[4], q[5]),
                                    pack_bf16(q[6], q[7]));
    });
    if (cx.wr) {
      sts32(cx.sa01 + PB * 640 + BLK * 64, alpha[0]);
      sts32(cx.sa01 + PB * 640 + BLK * 64 + 8, alpha[NR - 1]);
    }
  } else {
    static_for<0, 2>([&](auto G) {
      constexpr int g = decltype(G)::value;
      const float* q = s + g * 16;
      stsm4_o<(g << 6), PB * QCHUNK>(cx.pa2, pack_bf16(q[0], q[1]), pack_bf16(q[4], q[5]), pack_bf16(q[8], q[9]),
                           pack_bf16(q[12], q[13]));
    });
    if (cx.wr) sts32(cx.sa2 + PB * 640, alpha[0]);
  }
}

__device__ __forceinline__ void s_tile(int j, float* mc, float* l, SCtx& cx, int wi, int lane) {
  constexpr uint32_t sb = SB;
  float sX[32], sY[32];
  uint32_t flag = 0, slot, use;
  const uint32_t pb = j & 1;
  kv_slot(j == 0 ? 0 : 2 * j - 1, slot, use);
  mbar_wait(sb + BAR_FULL + 8 * slot, use & 1);
  if (wi == 0) PROF(8 + j);
  const uint32_t dk = dlo(sb + OFF_SLOT) + slot * (SLOT_B >> 4);
  qk_issue<0>(sX, dk);
  qk_issue<1>(sY, dk);
  if (j >= 2) nb_sync(NB_PEMPTY + pb, 384);
  if (j >= 1) nb_arrive(NB_GO, 256);
  wg_wait<1>();
  reg_fence<32>(sX);
  softmax_blk<0>(sX, mc, l, flag, cx, [] {});
  qk_issue<2>(sX, dk);
  if (j >= 1) nb_arrive(NB_GO + 1, 256);
  wg_wait<1>();
  reg_fence<32>(sY);
  softmax_blk<1>(sY, mc, l, flag, cx, [&] {
    wg_wait<0>();
    if (lane == 0) mbar_arrive_n(sb + BAR_EMPTY + 8 * slot, 2);
  });
  reg_fence<32>(sX);
  softmax_blk<2>(sX, mc, l, flag, cx, [] {});
  if (lane == 0) asm volatile("st.shared.u32 [%0], %1;" ::"r"(sb + OFF_FLAG + pb * 16 + wi * 4), "r"(flag) : "memory");
  fence_async();
  nb_arrive(NB_PFULL + pb, 384);
  const uint32_t dp = pb ? (0u - QCHUNK) : QCHUNK, ds = pb ? (0u - 640u) : 640u;
  cx.pa01 += dp; cx.pa2 += dp; cx.sa01 += ds; cx.sa2 += ds;
}

__global__ void __launch_bounds__(NTHREADS, 1)
fused_gqa_kernel(const __grid_constant__ Maps maps, __nv_bfloat16* __restrict__ out) {
  extern __shared__ uint8_t smem_raw[];
  constexpr uint32_t sb = SB;
  if ((uint32_t)__cvta_generic_to_shared(smem_raw) != sb) __trap();
  const int wg = __shfl_sync(0xffffffffu, threadIdx.x >> 7, 0);
#define ROLE_IDS()                                                   \
  int tid, bid;                                                      \
  asm volatile("mov.u32 %0, %%tid.x;" : "=r"(tid));                  \
  asm volatile("mov.u32 %0, %%ctaid.x;" : "=r"(bid));                \
  const int wi = __shfl_sync(0xffffffffu, (tid >> 5) & 3, 0);        \
  const int lane = tid & 31;                                         \
  const int blk = bid >> 6, kvh = (bid >> 3) & 7, b = bid & 7;       \
  (void)wi; (void)lane; (void)blk; (void)kvh; (void)b

  if (threadIdx.x == 0) {
    PROF(0);
    for (int s = 0; s < 4; s++) {
      mbar_init(sb + BAR_FULL + 8 * s, 1);
      mbar_init(sb + BAR_EMPTY + 8 * s, 8);
    }
    for (int s = 0; s < 6; s++) {
      mbar_init(sb + BAR_WFULL + 8 * s, 1);
      mbar_init(sb + BAR_WEMPT + 8 * s, 8);
    }
    mbar_init(sb + BAR_T, 1);
    asm volatile("fence.mbarrier_init.release.cluster;" ::: "memory");
    fence_async();
  }
  if (threadIdx.x < 32) {
    nb_arrive(0, 512);
    if (threadIdx.x == 0) {
      const int blk = blockIdx.x >> 6, kvh = (blockIdx.x >> 3) & 7, b = blockIdx.x & 7;
      const CUtensorMap* mx0 = &maps.m[blk * 5 + 0];
      const CUtensorMap* mw0 = &maps.m[blk * 5 + 3];
      static_for<0, NPRE>([&](auto T) {
        constexpr int t = decltype(T)::value, st = (t + 2) % 6, xc = t ? t - X_OFF : 0;
        constexpr bool hx = (t == 0) || (xc >= 1);
        mbar_expect_tx(sb + BAR_WFULL + 8 * st, hx ? WST_B + 10240 : WST_B);
        if constexpr (t == 0) tma3d(sb + OFF_Q, mx0, b * 80, 0, sb + BAR_WFULL + 8 * st);
        tma3d(sb + OFF_W + st * WST_B, mw0, 16 * t, kvh * 8, sb + BAR_WFULL + 8 * st);
        if constexpr (t > 0 && hx) tma3d(sb + OFF_Q + xc * 10240, mx0, b * 80, xc, sb + BAR_WFULL + 8 * st);
      });
    }
    __syncwarp();
  } else {
    nb_sync(0, 512);
  }

  if (wg == 0) {
    asm volatile("setmaxnreg.dec.sync.aligned.u32 24;");
    ROLE_IDS();
    if (tid >= 64 && tid < 68) {
      const CUtensorMap* m = (tid == 64) ? &maps.k8[blk] : &maps.m[blk * 5 + (tid == 65 ? 1 : tid == 66 ? 2 : 4)];
      asm volatile("prefetch.tensormap [%0];" ::"l"(m) : "memory");
    }
    if (wi == 3) {
      __nanosleep(ZERO_NS);
      __nv_bfloat16* o = out + (size_t)(b * 80 + kvh * 10) * 896 + blk * 448;
#pragma unroll 1
      for (int r = 0; r < 10; r++) {
        *reinterpret_cast<uint4*>(o + r * 896 + lane * 8) = make_uint4(0, 0, 0, 0);
        if (lane < 24) *reinterpret_cast<uint4*>(o + r * 896 + 256 + lane * 8) = make_uint4(0, 0, 0, 0);
      }
      __threadfence();
      __syncwarp();
      if (lane == 0) asm volatile("red.release.gpu.global.add.u32 [%0], 1;" ::"l"(g_zero + (blk * 8 + b) * 32) : "memory");
    }
    if (tid == 32) {
      const uint32_t epoch = (atomicAdd(&g_ticket, 1u) >> 7) + 1u;
      asm volatile("st.shared.u32 [%0], %1;" ::"r"(sb + OFF_MISC), "r"(epoch) : "memory");
      mbar_arrive(sb + BAR_T);
    }
    if (tid == 0) {
      const CUtensorMap* mk = &maps.m[blk * 5 + 1];
      const CUtensorMap* mv = &maps.m[blk * 5 + 2];
      const CUtensorMap* mwq = &maps.m[blk * 5 + 3];
      const CUtensorMap* mwo = &maps.m[blk * 5 + 4];
      const int row0 = (b * 8 + kvh) * 1024;
      uint32_t tstart;
      asm volatile("mov.u32 %0, %%globaltimer_lo;" : "=r"(tstart));
      uint64_t pol;
      asm volatile("createpolicy.fractional.L2::" KV_POL ".b64 %0, 1.0;" : "=l"(pol));
      const CUtensorMap* mx = &maps.m[blk * 5 + 0];
      uint32_t st = (NPRE + 2) % 6, ph = (NPRE == 6) ? 0 : 1;
#pragma unroll 1
      for (int t = NPRE; t < 28; t++) {
        if (t == WPF_A) tma3d_pf(mwq, 16 * (WPF_0 + b), kvh * 8);
        if (t == WPF_B) tma3d_pf(mwq, 16 * (WPF_0 + 8 + b), kvh * 8);
        if (t == WPF_C && WPF_0 + 16 + b < 28) tma3d_pf(mwq, 16 * (WPF_0 + 16 + b), kvh * 8);
        if (t >= K0_AT && ((t - K0_AT) % K_STEP) == 0 && (t - K0_AT) / K_STEP < 4) {
          const int q = (t - K0_AT) / K_STEP;
          if (q == 0) mbar_expect_tx(sb + BAR_FULL, SLOT_B);
          tma3d_ef(sb + OFF_SLOT + q * 8192, &maps.k8[blk], row0, q, sb + BAR_FULL, pol);
        }
        if (t >= 6) mbar_wait(sb + BAR_WEMPT + 8 * st, ph);
        const int xc = t - X_OFF;
        const bool hx = (xc >= 1 && xc < 7);
        mbar_expect_tx(sb + BAR_WFULL + 8 * st, hx ? WST_B + 10240 : WST_B);
        tma3d(sb + OFF_W + st * WST_B, mwq, 16 * t, kvh * 8, sb + BAR_WFULL + 8 * st);
        if (hx) tma3d(sb + OFF_Q + xc * 10240, mx, b * 80, xc, sb + BAR_WFULL + 8 * st);
        if (++st == 6) st = 0;
        if (st == 2) ph ^= 1;
      }
      mbar_wait(sb + BAR_WEMPT, 1);
      mbar_wait(sb + BAR_WEMPT + 8, 1);
      mbar_expect_tx(sb + BAR_FULL + 8, SLOT_B);
      tma3d_ef(sb + OFF_SLOT + SLOT_B, mk, row0 + 64, 0, sb + BAR_FULL + 8, pol);
      mbar_wait(sb + BAR_WEMPT + 16, 0);
      mbar_wait(sb + BAR_WEMPT + 24, 0);
#pragma unroll 1
      for (int i = 2; i < 32; i++) {
        uint32_t s, use;
        kv_slot(i, s, use);
        const int ii = (SWAP && (i >> 1) == 14) ? (i ^ 1) : i;
        const bool isv = !(ii & 1) || (ii == 31);
        const int j = (ii == 31) ? 15 : (isv ? ((ii - 2) >> 1) : ((ii + 1) >> 1));
        if (use > 0) mbar_wait(sb + BAR_EMPTY + 8 * s, (use - 1) & 1);
        if (i < PACE_END) {
          const uint32_t due = PACE_T0 + i * PACE_TAU;
          uint32_t now;
          do { asm volatile("mov.u32 %0, %%globaltimer_lo;" : "=r"(now)); } while (now - tstart < due);
        }
        mbar_expect_tx(sb + BAR_FULL + 8 * s, SLOT_B);
        tma3d_ef(sb + OFF_SLOT + s * SLOT_B, isv ? mv : mk, row0 + 64 * j, 0, sb + BAR_FULL + 8 * s, pol);
        if (i == WO_AT) {
          tma3d_pf(mwo, kvh * 512 + 256 * (b & 1), b >> 1);
          if (b < 6) tma3d_pf(mwo, kvh * 512 + 256 * (b & 1), 4 + (b >> 1));
        }
      }
#pragma unroll 1
      for (int u = 0; u < 14; u++) {
        uint32_t s, use;
        wo_slot(u, s, use);
        if (use > 0) mbar_wait(sb + BAR_EMPTY + 8 * s, (use - 1) & 1);
        mbar_expect_tx(sb + BAR_FULL + 8 * s, SLOT_B);
        tma3d(sb + OFF_SLOT + s * SLOT_B, mwo, kvh * 512 + 256 * (u & 1), u >> 1, sb + BAR_FULL + 8 * s);
      }
    }
  } else if (wg == 1) {
    asm volatile(SREG_STR);
    ROLE_IDS();
    float m[5], l[5];
#pragma unroll
    for (int r = 0; r < 5; r++) { m[r] = -INFINITY; l[r] = 0.f; }
    SCtx cx;
    {
      const uint32_t li = lane & 7, lm = lane >> 3;
      cx.pa01 = sb + OFF_P + (16 * wi + li + 8 * (lm & 1)) * 128 + (((lm >> 1) ^ li) << 4);
      cx.pa2 = sb + OFF_P + (128 + 8 * wi + li) * 128 + ((lm ^ li) << 4);
      const uint32_t r8 = lane >> 2;
      cx.sa01 = sb + OFF_SC + (40 * (r8 >> 1) + 2 * (2 * wi) + (r8 & 1)) * 4;
      cx.sa2 = sb + OFF_SC + (40 * (r8 >> 1) + 2 * (16 + wi) + (r8 & 1)) * 4;
      cx.wr = (lane & 3) == 0;
    }
    nb_sync(NB_Q, 384);
    if (tid == 128) PROF(3);
#pragma unroll 1
    for (int j = 0; j < 16; j++) s_tile(j, m, l, cx, wi, lane);
#pragma unroll
    for (int r = 0; r < 5; r++) {
      float lr = l[r];
      lr += __shfl_xor_sync(0xffffffffu, lr, 1);
      lr += __shfl_xor_sync(0xffffffffu, lr, 2);
      float inv;
      asm("rcp.approx.ftz.f32 %0, %1;" : "=f"(inv) : "f"(lr));
      if (cx.wr) sts32((r < 4 ? cx.sa01 + (r >> 1) * 64 + (r & 1) * 8 : cx.sa2) + (OFF_LINV - OFF_SC), inv);
    }
    nb_arrive(NB_O2, 384);
    uint32_t tid2, bid2;
    asm volatile("mov.u32 %0, %%tid.x;" : "=r"(tid2));
    asm volatile("mov.u32 %0, %%ctaid.x;" : "=r"(bid2));
    if (tid2 < 160) {
      if (tid2 == 128) {
        uint32_t epoch, z, it = 0;
        mbar_wait(sb + BAR_T, 0);
        asm volatile("ld.shared.u32 %0, [%1];" : "=r"(epoch) : "r"(sb + OFF_MISC) : "memory");
        do {
          asm volatile("ld.acquire.gpu.global.u32 %0, [%1];" : "=r"(z) : "l"(g_zero + ((bid2 >> 6) * 8 + (bid2 & 7)) * 32) : "memory");
          if (++it > (1u << 22)) __trap();
        } while ((int)(z - 8 * epoch) < 0);
        asm volatile("fence.proxy.async;" ::: "memory");
      }
#pragma unroll 1
      for (int p = 0; p < 7; p++) {
        nb_sync(NB_SF + (p & 1), 160);
        if (tid2 == 128) {
#pragma unroll
          for (int k = 4; k >= 0; k--) {
            asm volatile("cp.reduce.async.bulk.tensor.3d.global.shared::cta.add.tile.bulk_group [%0, {%1, %2, %3}], [%4];"
                         ::"l"(&maps.o), "r"(0), "r"((bid2 & 7) * 80 + 16 * k), "r"((bid2 >> 6) * 7 + p),
                         "r"(sb + OFF_ST + (k == 4 ? 16384 : (p & 1) * 8192 + k * 2048)) : "memory");
            if (k == 4 || k == 0) asm volatile("cp.async.bulk.commit_group;" ::: "memory");
          }
          asm volatile("cp.async.bulk.wait_group.read 1;" ::: "memory");
        }
        __syncwarp();
        if (p < 6) nb_arrive(nb_se((p + 1) & 1), 160);
        if (tid2 == 128) asm volatile("cp.async.bulk.wait_group.read 0;" ::: "memory");
        __syncwarp();
        if (p < 5) nb_arrive(NB_GO + (p & 1), 160);
      }
    }
    if (tid2 == 128) PROF(7);
  } else if (WITH_O) {
    asm volatile("setmaxnreg.inc.sync.aligned.u32 192;");
    ROLE_IDS();
    const int w = __shfl_sync(0xffffffffu, (tid >> 7) & 1, 0);
    const uint32_t li = lane & 7, lm = lane >> 3;
    {
      float acc[160];
#pragma unroll
      for (int i = 0; i < 160; i++) acc[i] = 0.f;
      reg_fence<160>(acc);
      if (tid == 256) PROF(1);
      uint32_t st = 2, ph = 0, pst = 0, ok = 0;
#pragma unroll 1
      for (int t = 0; t < 28; t++) {
        if (!ok) mbar_wait(sb + BAR_WFULL + 8 * st, ph);
        const uint32_t nst = (st == 5) ? 0 : st + 1, nph = (nst == 2) ? ph ^ 1 : ph;
        ok = QTEST ? mbar_test(sb + BAR_WFULL + 8 * nst, nph) : 0;
        const uint32_t da = dlo(sb + OFF_W) + st * (WST_B >> 4) + w * (8192 >> 4);
        const uint32_t db = dlo(sb + OFF_Q) + (((t >> 2) * 10240 + (t & 3) * 32) >> 4);
        wg_fence();
        static_for<0, 4>([&](auto C) { constexpr int cc = decltype(C)::value; wgmma_n80_mk1<cc * 2048, 0>(acc + 40 * cc, da, db); });
        wg_commit();
        wg_wait<1>();
        if (t > 0 && lane == 0) mbar_arrive(sb + BAR_WEMPT + 8 * pst);
        pst = st;
        st = nst;
        ph = nph;
      }
      wg_wait<0>();
      reg_fence<160>(acc);
      nb_sync(NB_O, 256);
      if (tid == 256) PROF(2);
      const uint32_t qa = sb + OFF_Q + (80 * w + 8 * (lm >> 1) + li) * 128 + (((2 * wi + (lm & 1)) ^ li) << 4);
#pragma unroll
      for (int cc = 0; cc < 4; cc++)
#pragma unroll
        for (int jj = 0; jj < 5; jj++) {
          const float* q = acc + 40 * cc + 8 * jj;
          stsm4t(qa + cc * QCHUNK + jj * 2048, pack_bf16(q[0], q[1]), pack_bf16(q[2], q[3]), pack_bf16(q[4], q[5]),
                 pack_bf16(q[6], q[7]));
        }
      fence_async();
      nb_arrive(NB_Q, 384);
    }
    {
    float acc[160];
#pragma unroll
    for (int i = 0; i < 160; i++) acc[i] = 0.f;
    reg_fence<160>(acc);
#pragma unroll 1
    for (int j = 0; j < 16; j++) {
      const uint32_t pb = j & 1;
      PO(52);
      nb_sync(NB_PFULL + pb, 384);
      PO(53);
      if (j > 0) {
        const float4 f = lds128(sb + OFF_FLAG + pb * 16);
        if ((__float_as_uint(f.x) | __float_as_uint(f.y) | __float_as_uint(f.z) | __float_as_uint(f.w)) != 0) {
          const uint32_t sc = sb + OFF_SC + pb * 640 + (lane & 3) * 160;
#pragma unroll
          for (int g = 0; g < 10; g++) {
            const float4 a = lds128(sc + g * 16);
#pragma unroll
            for (int mb = 0; mb < 2; mb++) {
              float* q = acc + 80 * mb + 8 * g;
              q[0] *= a.x; q[1] *= a.y; q[2] *= a.x; q[3] *= a.y;
              q[4] *= a.z; q[5] *= a.w; q[6] *= a.z; q[7] *= a.w;
            }
          }
        }
      }
      uint32_t slot, use;
      kv_slot(j == 15 ? 31 : (SWAP && j == 13) ? 29 : 2 * j + 2, slot, use);
      reg_fence<160>(acc);
      PO(54);
      if (j < 15) nb_sync(NB_GO + w, 256);
      else if (LAST_ORD && w == 1) nb_sync(NB_O, 256);
      mbar_wait(sb + BAR_FULL + 8 * slot, use & 1);
      if (tid == 256) PROF(24 + j);
      PO(55);
      const uint32_t da = dlo(sb + OFF_SLOT) + slot * (SLOT_B >> 4) + w * (16384 >> 4);
      const uint32_t db = dlo(sb + OFF_P) + pb * (QCHUNK >> 4);
      wg_fence();
      static_for<0, 4>([&](auto K) {
        constexpr int ks = decltype(K)::value;
        wgmma_n160_mk1<ks * 2048, ks * 32>(acc, da, db);
        wgmma_n160_mk1<8192 + ks * 2048, ks * 32>(acc + 80, da, db);
      });
      wg_commit();
      if (LAST_ORD && j == 15 && w == 0) nb_arrive(NB_O, 256);
      PO(56);
      wg_wait<0>();
      reg_fence<160>(acc);
      PO(57);
      if (lane == 0) mbar_arrive(sb + BAR_EMPTY + 8 * slot);
      if (j < 14) nb_arrive(NB_PEMPTY + pb, 384);
    }
    if (tid == 256) PROF(4);
    {
      const uint32_t oa = sb + OFF_Q + 2 * w * QCHUNK + (8 * (lm >> 1) + li) * 128 + (((2 * wi + (lm & 1)) ^ li) << 4);
#pragma unroll
      for (int mb = 0; mb < 2; mb++)
#pragma unroll
        for (int jj = 0; jj < 10; jj++) {
          const float* q = acc + 80 * mb + 8 * jj;
          stsm4t(oa + mb * QCHUNK + jj * 2048, pack_bf16(q[0], q[1]), pack_bf16(q[2], q[3]), pack_bf16(q[4], q[5]),
                 pack_bf16(q[6], q[7]));
        }
      fence_async();
    }
    }
    nb_sync(NB_O2, 384);
    if (tid == 256) PROF(5);
    constexpr uint32_t dob = dlo(sb + OFF_Q);
    const uint32_t sta = sb + OFF_ST + (8 * (lm >> 1) + li) * 128 + (((2 * wi + (lm & 1)) ^ li) << 4);
    float linv[40];
#pragma unroll
    for (int g = 0; g < 10; g++) {
      const float4 f = lds128(sb + OFF_LINV + (lane & 3) * 160 + g * 16);
      linv[4 * g] = f.x; linv[4 * g + 1] = f.y; linv[4 * g + 2] = f.z; linv[4 * g + 3] = f.w;
    }
#pragma unroll 1
    for (int p = w; p < 7; p += 2) {
      float acc[40], acc1[40];
      uint32_t slot0, use0, slot1, use1;
      wo_slot(2 * p, slot0, use0);
      wo_slot(2 * p + 1, slot1, use1);
      mbar_wait(sb + BAR_FULL + 8 * slot0, use0 & 1);
      if (p > 0) nb_sync(NB_ORD + w, 256);
      if (lane == 0 && wi == 0) PT(40 + p);
      uint32_t da = dlo(sb + OFF_SLOT) + slot0 * (SLOT_B >> 4);
      wg_fence();
      wgmma_n80_mk_z<0, 0>(acc, da, dob);
      static_for<1, TEST_KS>([&](auto K) {
        constexpr int ks = decltype(K)::value;
        wgmma_n80_mk1<ks * 2048, (ks >> 2) * QCHUNK + (ks & 3) * 32>(acc, da, dob);
      });
      const uint32_t ok1 = mbar_test(sb + BAR_FULL + 8 * slot1, use1 & 1);
      static_for<TEST_KS, 16>([&](auto K) {
        constexpr int ks = decltype(K)::value;
        wgmma_n80_mk1<ks * 2048, (ks >> 2) * QCHUNK + (ks & 3) * 32>(acc, da, dob);
      });
      wg_commit();
      if (!ok1) mbar_wait(sb + BAR_FULL + 8 * slot1, use1 & 1);
      da = dlo(sb + OFF_SLOT) + slot1 * (SLOT_B >> 4);
      wg_fence();
      wgmma_n80_mk_z<0, 10240>(acc1, da, dob);
      static_for<1, 6>([&](auto K) {
        constexpr int ks = decltype(K)::value;
        wgmma_n80_mk1<ks * 2048, 10240 + (ks >> 2) * QCHUNK + (ks & 3) * 32>(acc1, da, dob);
      });
      wg_commit();
      wg_wait<1>();
      if (lane == 0) mbar_arrive_n(sb + BAR_EMPTY + 8 * slot0, 2);
      wg_fence();
      static_for<6, 16>([&](auto K) {
        constexpr int ks = decltype(K)::value;
        wgmma_n80_mk1<ks * 2048, 10240 + (ks >> 2) * QCHUNK + (ks & 3) * 32>(acc1, da, dob);
      });
      wg_commit();
      if (p < 6) nb_arrive(NB_ORD + (w ^ 1), 256);
      wg_wait<0>();
      reg_fence<40>(acc);
      reg_fence<40>(acc1);
      if (lane == 0) mbar_arrive_n(sb + BAR_EMPTY + 8 * slot1, 2);
#pragma unroll
      for (int i = 0; i < 40; i++)
        acc[i] = fmaf(acc[i], linv[2 * (i >> 2) + (i & 1)], acc1[i] * linv[20 + 2 * (i >> 2) + (i & 1)]);
      uint32_t pk[20];
#pragma unroll
      for (int i = 0; i < 20; i++) pk[i] = pack_bf16(acc[2 * i], acc[2 * i + 1]);
      if (p > 1) nb_sync(NB_GO + w, 160);
#pragma unroll
      for (int k = 0; k < 4; k++) stsm4t(sta + w * 8192 + k * 2048, pk[4 * k], pk[4 * k + 1], pk[4 * k + 2], pk[4 * k + 3]);
      if (p > 0) nb_sync(nb_se(w), 160);
      stsm4t(sta + 16384, pk[16], pk[17], pk[18], pk[19]);
      fence_async();
      nb_arrive(NB_SF + w, 160);
      if (lane == 0 && wi == 0) PT(47 + p);
    }
    if (tid == 256) PROF(6);
    if (lane == 0 && wi == 0) PT(60 - w);
  }
}

typedef CUresult (*EncodeFn)(CUtensorMap*, CUtensorMapDataType, cuuint32_t, void*, const cuuint64_t*, const cuuint64_t*,
                             const cuuint32_t*, const cuuint32_t*, CUtensorMapInterleave, CUtensorMapSwizzle,
                             CUtensorMapL2promotion, CUtensorMapFloatOOBfill);

void encode3d(EncodeFn enc, CUtensorMap* m, void* p, uint64_t rows, uint64_t cols, uint32_t box_rows,
              uint32_t box_blocks) {
  cuuint64_t dims[3] = {64, rows, cols / 64};
  cuuint64_t strides[2] = {cols * 2, 128};
  cuuint32_t box[3] = {64, box_rows, box_blocks};
  cuuint32_t es[3] = {1, 1, 1};
  enc(m, CU_TENSOR_MAP_DATA_TYPE_BFLOAT16, 3, p, dims, strides, box, es, CU_TENSOR_MAP_INTERLEAVE_NONE,
      CU_TENSOR_MAP_SWIZZLE_128B, CU_TENSOR_MAP_L2_PROMOTION_L2_256B, CU_TENSOR_MAP_FLOAT_OOB_FILL_NONE);
}

}

extern "C" void kernel_launch(void* const* d_in, const int* in_sizes, int n_in, void* d_out, int out_size) {
  static EncodeFn enc = nullptr;
  if (!enc) {
    void* fn = nullptr;
    cudaDriverEntryPointQueryResult qr;
    cudaGetDriverEntryPoint("cuTensorMapEncodeTiled", &fn, cudaEnableDefault, &qr);
    enc = (EncodeFn)fn;
    cudaFuncSetAttribute(fused_gqa_kernel, cudaFuncAttributeMaxDynamicSharedMemorySize, SMEM_BYTES);
  }
  Maps maps;
  for (int blk = 0; blk < 2; blk++) {
    encode3d(enc, &maps.m[blk * 5 + 0], d_in[blk * 5 + 0], 640, 448, 80, 1);
    encode3d(enc, &maps.m[blk * 5 + 1], d_in[blk * 5 + 1], 65536, 256, 64, 4);
    encode3d(enc, &maps.m[blk * 5 + 2], d_in[blk * 5 + 2], 65536, 256, 64, 4);
    encode3d(enc, &maps.m[blk * 5 + 3], d_in[blk * 5 + 3], 448, 4096, 16, 8);
    encode3d(enc, &maps.m[blk * 5 + 4], d_in[blk * 5 + 4], 4096, 448, 256, 1);
    encode3d(enc, &maps.k8[blk], d_in[blk * 5 + 1], 65536, 256, 64, 1);
  }
  encode3d(enc, &maps.o, d_out, 640, 896, 16, 1);
  fused_gqa_kernel<<<NCTA, NTHREADS, SMEM_BYTES>>>(maps, (__nv_bfloat16*)d_out);
}
```

```cpp
#include <cuda_runtime.h>
#include <cuda_bf16.h>
#include <cuda.h>
#include <stdint.h>

namespace {

constexpr int NCTA = 128;
constexpr int NTHREADS = 512;

constexpr uint32_t SB = 0x400;
constexpr uint32_t OFF_Q     = 0;
constexpr uint32_t QCHUNK    = 20480;
constexpr uint32_t OFF_SLOT  = 81920;
constexpr uint32_t SLOT_B    = 32768;
constexpr uint32_t OFF_P     = OFF_SLOT + 3 * SLOT_B;
constexpr uint32_t OFF_W     = OFF_SLOT + SLOT_B;
constexpr uint32_t WST_B     = 16384;
constexpr uint32_t OFF_SC    = OFF_P + 2 * QCHUNK;
constexpr uint32_t OFF_FLAG  = OFF_SC + 1280;
constexpr uint32_t OFF_LINV  = OFF_FLAG + 32;
constexpr uint32_t OFF_ST    = OFF_P + SLOT_B;
constexpr uint32_t OFF_BAR   = OFF_ST + 18432;
constexpr uint32_t BAR_FULL  = OFF_BAR;
constexpr uint32_t BAR_EMPTY = BAR_FULL + 32;
constexpr uint32_t BAR_WFULL = BAR_EMPTY + 32;
constexpr uint32_t BAR_WEMPT = BAR_WFULL + 48;
constexpr uint32_t BAR_T     = BAR_WEMPT + 48;
constexpr uint32_t BAR_VL    = BAR_T + 8;
constexpr uint32_t OFF_MISC  = BAR_VL + 8;
constexpr uint32_t OFF_PROF  = OFF_MISC + 16;
constexpr uint32_t SMEM_USED = OFF_PROF + 256;
constexpr uint32_t SMEM_BYTES = SMEM_USED;

#define PACE_TAU 1340
#define PACE_T0 3400

#define LAZY_T 8.f
struct Maps {
  CUtensorMap m[10];
  CUtensorMap k8[2];
  CUtensorMap v16[2];
  CUtensorMap o;
};

__device__ unsigned int g_zero[16 * 32];
#define PT(idx) do {} while (0)
#define PROF(idx) do {} while (0)

__device__ __forceinline__ void mbar_init(uint32_t bar, uint32_t cnt) {
  asm volatile("mbarrier.init.shared::cta.b64 [%0], %1;" ::"r"(bar), "r"(cnt) : "memory");
}
__device__ __forceinline__ void mbar_expect_tx(uint32_t bar, uint32_t bytes) {
  asm volatile("mbarrier.arrive.expect_tx.shared::cta.b64 _, [%0], %1;" ::"r"(bar), "r"(bytes) : "memory");
}
__device__ __forceinline__ void mbar_arrive(uint32_t bar) {
  asm volatile("mbarrier.arrive.shared::cta.b64 _, [%0];" ::"r"(bar) : "memory");
}
__device__ __forceinline__ void mbar_arrive_n(uint32_t bar, uint32_t n) {
  asm volatile("mbarrier.arrive.shared::cta.b64 _, [%0], %1;" ::"r"(bar), "r"(n) : "memory");
}
__device__ __forceinline__ void mbar_wait(uint32_t bar, uint32_t parity) {
  asm volatile(
      "{\n.reg .pred p;\n.reg .u32 c;\nmov.u32 c, 0;\n"
      "W_LOOP:\n"
      "mbarrier.try_wait.parity.shared::cta.b64 p, [%0], %1;\n"
      "@p bra W_DONE;\n"
      "add.u32 c, c, 1;\n"
      "setp.lt.u32 p, c, 0x400000;\n"
      "@p bra W_LOOP;\n"
      "trap;\n"
      "W_DONE:\n}\n" ::"r"(bar), "r"(parity) : "memory");
}
__device__ __forceinline__ uint32_t mbar_test(uint32_t bar, uint32_t parity) {
  uint32_t ok;
  asm volatile("{\n.reg .pred p;\nmbarrier.test_wait.parity.shared::cta.b64 p, [%1], %2;\nselp.u32 %0, 1, 0, p;\n}\n"
               : "=r"(ok) : "r"(bar), "r"(parity) : "memory");
  return ok;
}
__device__ __forceinline__ void nb_sync(uint32_t id, uint32_t n) { asm volatile("bar.sync %0, %1;" ::"r"(id), "r"(n) : "memory"); }
__device__ __forceinline__ void nb_arrive(uint32_t id, uint32_t n) { asm volatile("bar.arrive %0, %1;" ::"r"(id), "r"(n) : "memory"); }
constexpr uint32_t NB_O = 1, NB_PFULL = 2, NB_PEMPTY = 4, NB_GO = 6, NB_Q = 8, NB_ORD = 10, NB_O2 = 12, NB_S = 13, NB_SF = 14;
__device__ __forceinline__ uint32_t nb_se(uint32_t w) { return w ? NB_S : NB_Q; }
__device__ __forceinline__ void tma3d(uint32_t dst, const CUtensorMap* m, int c1, int c2, uint32_t bar) {
  asm volatile(
      "cp.async.bulk.tensor.3d.shared::cluster.global.mbarrier::complete_tx::bytes [%0], [%1, {%2, %3, %4}], [%5];"
      ::"r"(dst), "l"(m), "r"(0), "r"(c1), "r"(c2), "r"(bar) : "memory");
}
__device__ __forceinline__ void tma3d_ef(uint32_t dst, const CUtensorMap* m, int c1, int c2, uint32_t bar, uint64_t pol) {
  asm volatile(
      "cp.async.bulk.tensor.3d.shared::cluster.global.mbarrier::complete_tx::bytes.L2::cache_hint [%0], [%1, {%2, %3, %4}], [%5], %6;"
      ::"r"(dst), "l"(m), "r"(0), "r"(c1), "r"(c2), "r"(bar), "l"(pol) : "memory");
}
__device__ __forceinline__ void tma3d_pf(const CUtensorMap* m, int c1, int c2) {
  asm volatile("cp.async.bulk.prefetch.tensor.3d.L2.global [%0, {%1, %2, %3}];" ::"l"(m), "r"(0), "r"(c1), "r"(c2)
               : "memory");
}
__device__ __forceinline__ void wg_fence() { asm volatile("wgmma.fence.sync.aligned;" ::: "memory"); }
__device__ __forceinline__ void wg_commit() { asm volatile("wgmma.commit_group.sync.aligned;" ::: "memory"); }
template <int N>
__device__ __forceinline__ void wg_wait() { asm volatile("wgmma.wait_group.sync.aligned %0;" ::"n"(N) : "memory"); }
__device__ __forceinline__ void fence_async() { asm volatile("fence.proxy.async.shared::cta;" ::: "memory"); }
template <int N>
__device__ __forceinline__ void reg_fence(float* d) {
#pragma unroll
  for (int i = 0; i < N; i++) asm volatile("" : "+f"(d[i])::"memory");
}
__device__ __forceinline__ constexpr uint32_t dlo(uint32_t saddr) { return ((saddr & 0x3FFFFu) >> 4) | (1u << 16); }
template <int V>
struct IC { static constexpr int value = V; };
template <int I, int N, class F>
__device__ __forceinline__ void static_for(F&& f) {
  if constexpr (I < N) {
    f(IC<I>{});
    static_for<I + 1, N>(f);
  }
}
__device__ __forceinline__ uint32_t pack_bf16(float lo, float hi) {
  uint32_t r;
  asm("cvt.rn.bf16x2.f32 %0, %1, %2;" : "=r"(r) : "f"(hi), "f"(lo));
  return r;
}
template <uint32_t XR, uint32_t OFF>
__device__ __forceinline__ void stsm4_o(uint32_t a, uint32_t r0, uint32_t r1, uint32_t r2, uint32_t r3) {
  asm volatile("{\n.reg .b32 t;\nxor.b32 t, %0, %6;\nstmatrix.sync.aligned.m8n8.x4.shared.b16 [t + %5], {%1, %2, %3, %4};\n}\n"
               ::"r"(a), "r"(r0), "r"(r1), "r"(r2), "r"(r3), "n"(OFF), "n"(XR) : "memory");
}
__device__ __forceinline__ void stsm4t(uint32_t a, uint32_t r0, uint32_t r1, uint32_t r2, uint32_t r3) {
  asm volatile("stmatrix.sync.aligned.m8n8.x4.trans.shared.b16 [%0], {%1, %2, %3, %4};" ::"r"(a), "r"(r0), "r"(r1),
               "r"(r2), "r"(r3) : "memory");
}
__device__ __forceinline__ float ex2(float x) {
  float y;
  asm("ex2.approx.ftz.f32 %0, %1;" : "=f"(y) : "f"(x));
  return y;
}
__device__ __forceinline__ float4 lds128(uint32_t a) {
  float4 v;
  asm volatile("ld.shared.v4.f32 {%0, %1, %2, %3}, [%4];" : "=f"(v.x), "=f"(v.y), "=f"(v.z), "=f"(v.w) : "r"(a) : "memory");
  return v;
}
__device__ __forceinline__ void sts32(uint32_t a, float v) {
  asm volatile("st.shared.f32 [%0], %1;" ::"r"(a), "f"(v) : "memory");
}
template <uint32_t OA, uint32_t OB, uint32_t HIA = 0x40000040u>
__device__ __forceinline__ void wgmma_n64_kk_z(float* d, uint32_t a, uint32_t b) {
  asm volatile(
      "{\n.reg .b32 ta, tb;\n.reg .b64 da, db;\nadd.u32 ta, %32, %34;\nadd.u32 tb, %33, %35;\nmov.b64 da, {ta, %36};\nmov.b64 db, {tb, 0x40000040};\n"
      "wgmma.mma_async.sync.aligned.m64n64k16.f32.bf16.bf16 {"
      "%0, %1, %2, %3, %4, %5, %6, %7, %8, %9, %10, %11, %12, %13, %14, %15,"
      "%16, %17, %18, %19, %20, %21, %22, %23, %24, %25, %26, %27, %28, %29, %30, %31}, da, db, 0, 1, 1, 0, 0;\n}\n"
      : "=f"(d[0]), "=f"(d[1]), "=f"(d[2]), "=f"(d[3]), "=f"(d[4]), "=f"(d[5]), "=f"(d[6]), "=f"(d[7]),
        "=f"(d[8]), "=f"(d[9]), "=f"(d[10]), "=f"(d[11]), "=f"(d[12]), "=f"(d[13]), "=f"(d[14]), "=f"(d[15]),
        "=f"(d[16]), "=f"(d[17]), "=f"(d[18]), "=f"(d[19]), "=f"(d[20]), "=f"(d[21]), "=f"(d[22]), "=f"(d[23]),
        "=f"(d[24]), "=f"(d[25]), "=f"(d[26]), "=f"(d[27]), "=f"(d[28]), "=f"(d[29]), "=f"(d[30]), "=f"(d[31])
      : "r"(a), "r"(b), "n"(OA >> 4), "n"(OB >> 4), "n"(HIA));
}

template <uint32_t OA, uint32_t OB, uint32_t HIA = 0x40000040u>
__device__ __forceinline__ void wgmma_n64_kk(float* d, uint32_t a, uint32_t b) {
  asm volatile(
      "{\n.reg .b32 ta, tb;\n.reg .b64 da, db;\nadd.u32 ta, %32, %34;\nadd.u32 tb, %33, %35;\nmov.b64 da, {ta, %36};\nmov.b64 db, {tb, 0x40000040};\n"
      "wgmma.mma_async.sync.aligned.m64n64k16.f32.bf16.bf16 {"
      "%0, %1, %2, %3, %4, %5, %6, %7, %8, %9, %10, %11, %12, %13, %14, %15,"
      "%16, %17, %18, %19, %20, %21, %22, %23, %24, %25, %26, %27, %28, %29, %30, %31}, da, db, 1, 1, 1, 0, 0;\n}\n"
      : "+f"(d[0]), "+f"(d[1]), "+f"(d[2]), "+f"(d[3]), "+f"(d[4]), "+f"(d[5]), "+f"(d[6]), "+f"(d[7]),
        "+f"(d[8]), "+f"(d[9]), "+f"(d[10]), "+f"(d[11]), "+f"(d[12]), "+f"(d[13]), "+f"(d[14]), "+f"(d[15]),
        "+f"(d[16]), "+f"(d[17]), "+f"(d[18]), "+f"(d[19]), "+f"(d[20]), "+f"(d[21]), "+f"(d[22]), "+f"(d[23]),
        "+f"(d[24]), "+f"(d[25]), "+f"(d[26]), "+f"(d[27]), "+f"(d[28]), "+f"(d[29]), "+f"(d[30]), "+f"(d[31])
      : "r"(a), "r"(b), "n"(OA >> 4), "n"(OB >> 4), "n"(HIA));
}

template <uint32_t OA, uint32_t OB, uint32_t HIA = 0x40000040u>
__device__ __forceinline__ void wgmma_n80_mk_z(float* d, uint32_t a, uint32_t b) {
  asm volatile(
      "{\n.reg .b32 ta, tb;\n.reg .b64 da, db;\nadd.u32 ta, %40, %42;\nadd.u32 tb, %41, %43;\nmov.b64 da, {ta, %44};\nmov.b64 db, {tb, 0x40000040};\n"
      "wgmma.mma_async.sync.aligned.m64n80k16.f32.bf16.bf16 {"
      "%0, %1, %2, %3, %4, %5, %6, %7, %8, %9, %10, %11, %12, %13, %14, %15,"
      "%16, %17, %18, %19, %20, %21, %22, %23, %24, %25, %26, %27, %28, %29, %30, %31,"
      "%32, %33, %34, %35, %36, %37, %38, %39}, da, db, 0, 1, 1, 1, 0;\n}\n"
      : "=f"(d[0]), "=f"(d[1]), "=f"(d[2]), "=f"(d[3]), "=f"(d[4]), "=f"(d[5]), "=f"(d[6]), "=f"(d[7]),
        "=f"(d[8]), "=f"(d[9]), "=f"(d[10]), "=f"(d[11]), "=f"(d[12]), "=f"(d[13]), "=f"(d[14]), "=f"(d[15]),
        "=f"(d[16]), "=f"(d[17]), "=f"(d[18]), "=f"(d[19]), "=f"(d[20]), "=f"(d[21]), "=f"(d[22]), "=f"(d[23]),
        "=f"(d[24]), "=f"(d[25]), "=f"(d[26]), "=f"(d[27]), "=f"(d[28]), "=f"(d[29]), "=f"(d[30]), "=f"(d[31]),
        "=f"(d[32]), "=f"(d[33]), "=f"(d[34]), "=f"(d[35]), "=f"(d[36]), "=f"(d[37]), "=f"(d[38]), "=f"(d[39])
      : "r"(a), "r"(b), "n"(OA >> 4), "n"(OB >> 4), "n"(HIA));
}

template <uint32_t OA, uint32_t OB, uint32_t HIA = 0x40000040u>
__device__ __forceinline__ void wgmma_n80_mk1(float* d, uint32_t a, uint32_t b) {
  asm volatile(
      "{\n.reg .b32 ta, tb;\n.reg .b64 da, db;\nadd.u32 ta, %40, %42;\nadd.u32 tb, %41, %43;\nmov.b64 da, {ta, %44};\nmov.b64 db, {tb, 0x40000040};\n"
      "wgmma.mma_async.sync.aligned.m64n80k16.f32.bf16.bf16 {"
      "%0, %1, %2, %3, %4, %5, %6, %7, %8, %9, %10, %11, %12, %13, %14, %15,"
      "%16, %17, %18, %19, %20, %21, %22, %23, %24, %25, %26, %27, %28, %29, %30, %31,"
      "%32, %33, %34, %35, %36, %37, %38, %39}, da, db, 1, 1, 1, 1, 0;\n}\n"
      : "+f"(d[0]), "+f"(d[1]), "+f"(d[2]), "+f"(d[3]), "+f"(d[4]), "+f"(d[5]), "+f"(d[6]), "+f"(d[7]),
        "+f"(d[8]), "+f"(d[9]), "+f"(d[10]), "+f"(d[11]), "+f"(d[12]), "+f"(d[13]), "+f"(d[14]), "+f"(d[15]),
        "+f"(d[16]), "+f"(d[17]), "+f"(d[18]), "+f"(d[19]), "+f"(d[20]), "+f"(d[21]), "+f"(d[22]), "+f"(d[23]),
        "+f"(d[24]), "+f"(d[25]), "+f"(d[26]), "+f"(d[27]), "+f"(d[28]), "+f"(d[29]), "+f"(d[30]), "+f"(d[31]),
        "+f"(d[32]), "+f"(d[33]), "+f"(d[34]), "+f"(d[35]), "+f"(d[36]), "+f"(d[37]), "+f"(d[38]), "+f"(d[39])
      : "r"(a), "r"(b), "n"(OA >> 4), "n"(OB >> 4), "n"(HIA));
}

template <uint32_t OA, uint32_t OB, uint32_t HIA = 0x40000040u>
__device__ __forceinline__ void wgmma_n160_mk1(float* d, uint32_t a, uint32_t b) {
  asm volatile(
      "{\n.reg .b32 ta, tb;\n.reg .b64 da, db;\nadd.u32 ta, %80, %82;\nadd.u32 tb, %81, %83;\nmov.b64 da, {ta, %84};\nmov.b64 db, {tb, 0x40000040};\n"
      "wgmma.mma_async.sync.aligned.m64n160k16.f32.bf16.bf16 {"
      "%0, %1, %2, %3, %4, %5, %6, %7, %8, %9, %10, %11, %12, %13, %14, %15,"
      "%16, %17, %18, %19, %20, %21, %22, %23, %24, %25, %26, %27, %28, %29, %30, %31,"
      "%32, %33, %34, %35, %36, %37, %38, %39, %40, %41, %42, %43, %44, %45, %46, %47,"
      "%48, %49, %50, %51, %52, %53, %54, %55, %56, %57, %58, %59, %60, %61, %62, %63,"
      "%64, %65, %66, %67, %68, %69, %70, %71, %72, %73, %74, %75, %76, %77, %78, %79}, da, db, 1, 1, 1, 1, 0;\n}\n"
      : "+f"(d[0]), "+f"(d[1]), "+f"(d[2]), "+f"(d[3]), "+f"(d[4]), "+f"(d[5]), "+f"(d[6]), "+f"(d[7]),
        "+f"(d[8]), "+f"(d[9]), "+f"(d[10]), "+f"(d[11]), "+f"(d[12]), "+f"(d[13]), "+f"(d[14]), "+f"(d[15]),
        "+f"(d[16]), "+f"(d[17]), "+f"(d[18]), "+f"(d[19]), "+f"(d[20]), "+f"(d[21]), "+f"(d[22]), "+f"(d[23]),
        "+f"(d[24]), "+f"(d[25]), "+f"(d[26]), "+f"(d[27]), "+f"(d[28]), "+f"(d[29]), "+f"(d[30]), "+f"(d[31]),
        "+f"(d[32]), "+f"(d[33]), "+f"(d[34]), "+f"(d[35]), "+f"(d[36]), "+f"(d[37]), "+f"(d[38]), "+f"(d[39]),
        "+f"(d[40]), "+f"(d[41]), "+f"(d[42]), "+f"(d[43]), "+f"(d[44]), "+f"(d[45]), "+f"(d[46]), "+f"(d[47]),
        "+f"(d[48]), "+f"(d[49]), "+f"(d[50]), "+f"(d[51]), "+f"(d[52]), "+f"(d[53]), "+f"(d[54]), "+f"(d[55]),
        "+f"(d[56]), "+f"(d[57]), "+f"(d[58]), "+f"(d[59]), "+f"(d[60]), "+f"(d[61]), "+f"(d[62]), "+f"(d[63]),
        "+f"(d[64]), "+f"(d[65]), "+f"(d[66]), "+f"(d[67]), "+f"(d[68]), "+f"(d[69]), "+f"(d[70]), "+f"(d[71]),
        "+f"(d[72]), "+f"(d[73]), "+f"(d[74]), "+f"(d[75]), "+f"(d[76]), "+f"(d[77]), "+f"(d[78]), "+f"(d[79])
      : "r"(a), "r"(b), "n"(OA >> 4), "n"(OB >> 4), "n"(HIA));
}

__device__ __forceinline__ void kv_slot(int i, uint32_t& slot, uint32_t& use) {
  use = (uint32_t)i / 3u;
  slot = (uint32_t)i - use * 3u;
}
__device__ __forceinline__ void wo_slot(int u, uint32_t& slot, uint32_t& use) {
  uint32_t r = u & 3, q = u >> 2;
  slot = (r == 0) ? 2u : (r == 3) ? 3u : (r - 1u);
  use = q + ((r == 0) ? 10u : (r == 3) ? 0u : 11u);
}

struct SCtx {
  uint32_t pa01, pa2, sa01, sa2;
  bool wr;
};

template <int BLK>
__device__ __forceinline__ void qk_issue(float* s, uint32_t dk) {
  constexpr uint32_t dq = dlo(SB + OFF_Q + BLK * 8192);
  constexpr uint32_t HI = (BLK == 2) ? 0x40000020u : 0x40000040u;
  wg_fence();
  constexpr uint32_t T = BLK << 20;
  wgmma_n64_kk_z<0, T, HI>(s, dq, dk);
  static_for<1, 16>([&](auto I) {
    constexpr int ks = decltype(I)::value;
    wgmma_n64_kk<(ks >> 2) * QCHUNK + (ks & 3) * 32, T + (ks >> 2) * 8192 + (ks & 3) * 32, HI>(s, dq, dk);
  });
  wg_commit();
}

template <int BLK, class F>
__device__ __forceinline__ void softmax_blk(float* s, float* mc, float* l, uint32_t& flag, const SCtx& cx, F&& mid) {
  constexpr float c = 0.0625f * 1.4426950408889634f;
  constexpr int NR = (BLK == 2) ? 1 : 2;
  float mx[NR], alpha[NR];
  bool need = false;
#pragma unroll
  for (int r = 0; r < NR; r++) {
    float v0 = fmaxf(s[2 * r], s[2 * r + 1]), v1 = fmaxf(s[2 * r + 4], s[2 * r + 5]);
#pragma unroll
    for (int g = 2; g < 8; g += 2) {
      v0 = fmaxf(v0, fmaxf(s[2 * r + 4 * g], s[2 * r + 4 * g + 1]));
      v1 = fmaxf(v1, fmaxf(s[2 * r + 4 * g + 4], s[2 * r + 4 * g + 5]));
    }
    mx[r] = fmaxf(v0, v1) * c;
    need |= !(mx[r] - mc[2 * BLK + r] <= LAZY_T);
    alpha[r] = 1.f;
  }
  if (__any_sync(0xffffffffu, need)) {
#pragma unroll
    for (int r = 0; r < NR; r++) mx[r] = fmaxf(mx[r], __shfl_xor_sync(0xffffffffu, mx[r], 1));
#pragma unroll
    for (int r = 0; r < NR; r++) mx[r] = fmaxf(mx[r], __shfl_xor_sync(0xffffffffu, mx[r], 2));
#pragma unroll
    for (int r = 0; r < NR; r++) {
      const float mo = mc[2 * BLK + r];
      const float mn = fmaxf(mo, mx[r]);
      alpha[r] = ex2(mo - mn);
      mc[2 * BLK + r] = mn;
      l[2 * BLK + r] *= alpha[r];
    }
    flag = 1;
  }
#pragma unroll
  for (int r = 0; r < NR; r++) {
    const float nm = -mc[2 * BLK + r];
    float sum0 = l[2 * BLK + r], sum1 = 0.f;
#pragma unroll
    for (int g = 0; g < 8; g++) {
      const float p0 = ex2(fmaf(s[2 * r + 4 * g], c, nm));
      const float p1 = ex2(fmaf(s[2 * r + 4 * g + 1], c, nm));
      s[2 * r + 4 * g] = p0;
      s[2 * r + 4 * g + 1] = p1;
      sum0 += p0;
      sum1 += p1;
    }
    const float lr = sum0 + sum1;
    l[2 * BLK + r] = lr;
    alpha[r] = fmaf(lr, 0.f, alpha[r]);
    if (r == 0) mid();
  }
  if (BLK < 2) {
    static_for<0, 4>([&](auto G) {
      constexpr int g = decltype(G)::value;
      const float* q = s + g * 8;
      stsm4_o<(g << 5), BLK * 8192>(cx.pa01, pack_bf16(q[0], q[1]), pack_bf16(q[2], q[3]), pack_bf16(q[4], q[5]),
                                    pack_bf16(q[6], q[7]));
    });
    if (cx.wr) {
      sts32(cx.sa01 + BLK * 64, alpha[0]);
      sts32(cx.sa01 + BLK * 64 + 8, alpha[NR - 1]);
    }
  } else {
    static_for<0, 2>([&](auto G) {
      constexpr int g = decltype(G)::value;
      const float* q = s + g * 16;
      stsm4_o<(g << 6), 0>(cx.pa2, pack_bf16(q[0], q[1]), pack_bf16(q[4], q[5]), pack_bf16(q[8], q[9]),
                           pack_bf16(q[12], q[13]));
    });
    if (cx.wr) sts32(cx.sa2, alpha[0]);
  }
}

__device__ __forceinline__ void s_tile(int j, float* mc, float* l, SCtx& cx, int wi, int lane) {
  constexpr uint32_t sb = SB;
  float sX[32], sY[32];
  uint32_t flag = 0, slot, use;
  const uint32_t pb = j & 1;
  kv_slot(j == 0 ? 0 : 2 * j - 1, slot, use);
  mbar_wait(sb + BAR_FULL + 8 * slot, use & 1);
  if (wi == 0) PROF(8 + j);
  const uint32_t dk = dlo(sb + OFF_SLOT) + slot * (SLOT_B >> 4);
  qk_issue<0>(sX, dk);
  qk_issue<1>(sY, dk);
  if (j >= 2) nb_sync(NB_PEMPTY + pb, 384);
  if (j >= 1) nb_arrive(NB_GO, 256);
  wg_wait<1>();
  reg_fence<32>(sX);
  softmax_blk<0>(sX, mc, l, flag, cx, [] {});
  qk_issue<2>(sX, dk);
  if (j >= 1) nb_arrive(NB_GO + 1, 256);
  wg_wait<1>();
  reg_fence<32>(sY);
  softmax_blk<1>(sY, mc, l, flag, cx, [&] {
    wg_wait<0>();
    if (lane == 0) mbar_arrive_n(sb + BAR_EMPTY + 8 * slot, 2);
  });
  reg_fence<32>(sX);
  softmax_blk<2>(sX, mc, l, flag, cx, [] {});
  if (lane == 0) asm volatile("st.shared.u32 [%0], %1;" ::"r"(sb + OFF_FLAG + pb * 16 + wi * 4), "r"(flag) : "memory");
  fence_async();
  nb_arrive(NB_PFULL + pb, 384);
  const uint32_t dp = pb ? (0u - QCHUNK) : QCHUNK, ds = pb ? (0u - 640u) : 640u;
  cx.pa01 += dp; cx.pa2 += dp; cx.sa01 += ds; cx.sa2 += ds;
}

__global__ void __launch_bounds__(NTHREADS, 1)
fused_gqa_kernel(const __grid_constant__ Maps maps, __nv_bfloat16* __restrict__ out) {
  extern __shared__ uint8_t smem_raw[];
  constexpr uint32_t sb = SB;
  if ((uint32_t)__cvta_generic_to_shared(smem_raw) != sb) __trap();
  const int wg = __shfl_sync(0xffffffffu, threadIdx.x >> 7, 0);
#define ROLE_IDS()                                                   \
  int tid, bid;                                                      \
  asm volatile("mov.u32 %0, %%tid.x;" : "=r"(tid));                  \
  asm volatile("mov.u32 %0, %%ctaid.x;" : "=r"(bid));                \
  const int wi = __shfl_sync(0xffffffffu, (tid >> 5) & 3, 0);        \
  const int lane = tid & 31;                                         \
  const int blk = bid >> 6, kvh = (bid >> 3) & 7, b = bid & 7;       \
  (void)wi; (void)lane; (void)blk; (void)kvh; (void)b

  if (threadIdx.x == 0) {
    PROF(0);
    for (int s = 0; s < 4; s++) {
      mbar_init(sb + BAR_FULL + 8 * s, 1);
      mbar_init(sb + BAR_EMPTY + 8 * s, 8);
    }
    for (int s = 0; s < 6; s++) {
      mbar_init(sb + BAR_WFULL + 8 * s, 1);
      mbar_init(sb + BAR_WEMPT + 8 * s, 8);
    }
    mbar_init(sb + BAR_T, 1);
    mbar_init(sb + BAR_VL, 1);
    asm volatile("fence.mbarrier_init.release.cluster;" ::: "memory");
    fence_async();
  }
  if (threadIdx.x < 32) {
    nb_arrive(0, 512);
    if (threadIdx.x == 0) {
      const int blk = blockIdx.x >> 6, kvh = (blockIdx.x >> 3) & 7, b = blockIdx.x & 7;
      const CUtensorMap* mx0 = &maps.m[blk * 5 + 0];
      const CUtensorMap* mw0 = &maps.m[blk * 5 + 3];
      static_for<0, 6>([&](auto T) {
        constexpr int t = decltype(T)::value, st = (t + 2) % 6, xc = t ? t - 1 : 0;
        constexpr bool hx = (t == 0) || (xc >= 1);
        mbar_expect_tx(sb + BAR_WFULL + 8 * st, hx ? WST_B + 10240 : WST_B);
        if constexpr (t == 0) tma3d(sb + OFF_Q, mx0, b * 80, 0, sb + BAR_WFULL + 8 * st);
        tma3d(sb + OFF_W + st * WST_B, mw0, 16 * t, kvh * 8, sb + BAR_WFULL + 8 * st);
        if constexpr (t > 0 && hx) tma3d(sb + OFF_Q + xc * 10240, mx0, b * 80, xc, sb + BAR_WFULL + 8 * st);
      });
    }
    __syncwarp();
  } else {
    nb_sync(0, 512);
  }

  if (wg == 0) {
    asm volatile("setmaxnreg.dec.sync.aligned.u32 24;");
    ROLE_IDS();
    if (tid >= 64 && tid < 70) {
      const CUtensorMap* m = (tid == 64) ? &maps.k8[blk] : (tid == 68) ? &maps.v16[blk] : (tid == 69) ? &maps.o
                                                         : &maps.m[blk * 5 + (tid == 65 ? 1 : tid == 66 ? 2 : 4)];
      asm volatile("prefetch.tensormap [%0];" ::"l"(m) : "memory");
    }
    if (wi == 3) {
      __nanosleep(20000);
      __nv_bfloat16* o = out + (size_t)(b * 80 + kvh * 10) * 896 + blk * 448;
#pragma unroll 1
      for (int r = 0; r < 10; r++) {
        *reinterpret_cast<uint4*>(o + r * 896 + lane * 8) = make_uint4(0, 0, 0, 0);
        if (lane < 24) *reinterpret_cast<uint4*>(o + r * 896 + 256 + lane * 8) = make_uint4(0, 0, 0, 0);
      }
      __threadfence();
      __syncwarp();
      if (lane == 0) {
        uint32_t old;
        asm volatile("atom.release.gpu.global.add.u32 %0, [%1], 1;" : "=r"(old) : "l"(g_zero + (blk * 8 + b) * 32) : "memory");
        asm volatile("st.shared.u32 [%0], %1;" ::"r"(sb + OFF_MISC), "r"((old | 7u) + 1u) : "memory");
        mbar_arrive(sb + BAR_T);
      }
    }
    if (tid == 0) {
      const CUtensorMap* mk = &maps.m[blk * 5 + 1];
      const CUtensorMap* mv = &maps.m[blk * 5 + 2];
      const CUtensorMap* mwq = &maps.m[blk * 5 + 3];
      const CUtensorMap* mwo = &maps.m[blk * 5 + 4];
      const int row0 = (b * 8 + kvh) * 1024;
      uint32_t tstart;
      asm volatile("mov.u32 %0, %%globaltimer_lo;" : "=r"(tstart));
      uint64_t pol;
      asm volatile("createpolicy.fractional.L2::evict_first.b64 %0, 1.0;" : "=l"(pol));
      const CUtensorMap* mx = &maps.m[blk * 5 + 0];
      uint32_t st = 2, ph = 0;
#pragma unroll 1
      for (int t = 6; t < 28; t++) {
        if (t == 6) tma3d_pf(mwq, 16 * (8 + b), kvh * 8);
        if (t == 9) tma3d_pf(mwq, 16 * (16 + b), kvh * 8);
        if (t == 12 && b < 4) tma3d_pf(mwq, 16 * (24 + b), kvh * 8);
        if (t >= 16 && t < 24 && !(t & 1)) {
          const int q = (t - 16) >> 1;
          if (q == 0) mbar_expect_tx(sb + BAR_FULL, SLOT_B);
          tma3d_ef(sb + OFF_SLOT + q * 8192, &maps.k8[blk], row0, q, sb + BAR_FULL, pol);
        }
        mbar_wait(sb + BAR_WEMPT + 8 * st, ph);
        const int xc = t - 1;
        const bool hx = xc < 7;
        mbar_expect_tx(sb + BAR_WFULL + 8 * st, hx ? WST_B + 10240 : WST_B);
        tma3d(sb + OFF_W + st * WST_B, mwq, 16 * t, kvh * 8, sb + BAR_WFULL + 8 * st);
        if (hx) tma3d(sb + OFF_Q + xc * 10240, mx, b * 80, xc, sb + BAR_WFULL + 8 * st);
        if (++st == 6) st = 0;
        if (st == 2) ph ^= 1;
      }
      mbar_wait(sb + BAR_WEMPT, 1);
      mbar_wait(sb + BAR_WEMPT + 8, 1);
      mbar_expect_tx(sb + BAR_FULL + 8, SLOT_B);
      tma3d_ef(sb + OFF_SLOT + SLOT_B, mk, row0 + 64, 0, sb + BAR_FULL + 8, pol);
      mbar_wait(sb + BAR_WEMPT + 16, 0);
      mbar_wait(sb + BAR_WEMPT + 24, 0);
#pragma unroll 1
      for (int i = 2; i < 32; i++) {
        uint32_t s, use;
        kv_slot(i, s, use);
        const bool isv = !(i & 1);
        const int j = isv ? ((i - 2) >> 1) : ((i + 1) >> 1);
        if (use > 0) mbar_wait(sb + BAR_EMPTY + 8 * s, (use - 1) & 1);
        {
          const uint32_t due = PACE_T0 + i * PACE_TAU;
          uint32_t now;
          do { asm volatile("mov.u32 %0, %%globaltimer_lo;" : "=r"(now)); } while (now - tstart < due);
        }
        if (i == 31) {
          mbar_expect_tx(sb + BAR_VL, SLOT_B / 2);
          tma3d_ef(sb + OFF_SLOT + s * SLOT_B, &maps.v16[blk], row0 + 960, 0, sb + BAR_VL, pol);
          mbar_expect_tx(sb + BAR_FULL + 8 * s, SLOT_B / 2);
          tma3d_ef(sb + OFF_SLOT + s * SLOT_B + SLOT_B / 2, &maps.v16[blk], row0 + 960, 2, sb + BAR_FULL + 8 * s, pol);
          break;
        }
        mbar_expect_tx(sb + BAR_FULL + 8 * s, SLOT_B);
        tma3d_ef(sb + OFF_SLOT + s * SLOT_B, isv ? mv : mk, row0 + 64 * j, 0, sb + BAR_FULL + 8 * s, pol);
      }
#pragma unroll 1
      for (int u = 0; u < 14; u++) {
        uint32_t s, use;
        wo_slot(u, s, use);
        if (use > 0) mbar_wait(sb + BAR_EMPTY + 8 * s, (use - 1) & 1);
        mbar_expect_tx(sb + BAR_FULL + 8 * s, SLOT_B);
        tma3d(sb + OFF_SLOT + s * SLOT_B, mwo, kvh * 512 + 256 * (u & 1), u >> 1, sb + BAR_FULL + 8 * s);
      }
    }
  } else if (wg == 1) {
    asm volatile("setmaxnreg.dec.sync.aligned.u32 104;");
    ROLE_IDS();
    float m[5], l[5];
#pragma unroll
    for (int r = 0; r < 5; r++) { m[r] = -INFINITY; l[r] = 0.f; }
    SCtx cx;
    {
      const uint32_t li = lane & 7, lm = lane >> 3;
      cx.pa01 = sb + OFF_P + (16 * wi + li + 8 * (lm & 1)) * 128 + (((lm >> 1) ^ li) << 4);
      cx.pa2 = sb + OFF_P + (128 + 8 * wi + li) * 128 + ((lm ^ li) << 4);
      const uint32_t r8 = lane >> 2;
      cx.sa01 = sb + OFF_SC + (40 * (r8 >> 1) + 2 * (2 * wi) + (r8 & 1)) * 4;
      cx.sa2 = sb + OFF_SC + (40 * (r8 >> 1) + 2 * (16 + wi) + (r8 & 1)) * 4;
      cx.wr = (lane & 3) == 0;
    }
    nb_sync(NB_Q, 384);
    if (tid == 128) PROF(3);
#pragma unroll 1
    for (int j = 0; j < 16; j++) s_tile(j, m, l, cx, wi, lane);
#pragma unroll
    for (int r = 0; r < 5; r++) {
      float lr = l[r];
      lr += __shfl_xor_sync(0xffffffffu, lr, 1);
      lr += __shfl_xor_sync(0xffffffffu, lr, 2);
      float inv;
      asm("rcp.approx.ftz.f32 %0, %1;" : "=f"(inv) : "f"(lr));
      if (cx.wr) sts32((r < 4 ? cx.sa01 + (r >> 1) * 64 + (r & 1) * 8 : cx.sa2) + (OFF_LINV - OFF_SC), inv);
    }
    nb_arrive(NB_O2, 384);
    uint32_t tid2, bid2;
    asm volatile("mov.u32 %0, %%tid.x;" : "=r"(tid2));
    asm volatile("mov.u32 %0, %%ctaid.x;" : "=r"(bid2));
    if (tid2 < 160) {
      if (tid2 == 128) {
        uint32_t target, z, it = 0;
        mbar_wait(sb + BAR_T, 0);
        asm volatile("ld.shared.u32 %0, [%1];" : "=r"(target) : "r"(sb + OFF_MISC) : "memory");
        do {
          asm volatile("ld.acquire.gpu.global.u32 %0, [%1];" : "=r"(z) : "l"(g_zero + ((bid2 >> 6) * 8 + (bid2 & 7)) * 32) : "memory");
          if (++it > (1u << 22)) __trap();
        } while ((int)(z - target) < 0);
        asm volatile("fence.proxy.async;" ::: "memory");
      }
#pragma unroll 1
      for (int p = 0; p < 7; p++) {
        nb_sync(NB_SF + (p & 1), 160);
        if (tid2 == 128) {
#pragma unroll
          for (int k = 4; k >= 0; k--) {
            asm volatile("cp.reduce.async.bulk.tensor.3d.global.shared::cta.add.tile.bulk_group [%0, {%1, %2, %3}], [%4];"
                         ::"l"(&maps.o), "r"(0), "r"((bid2 & 7) * 80 + 16 * k), "r"((bid2 >> 6) * 7 + p),
                         "r"(sb + OFF_ST + (k == 4 ? 16384 : (p & 1) * 8192 + k * 2048)) : "memory");
            if (k == 4 || k == 0) asm volatile("cp.async.bulk.commit_group;" ::: "memory");
          }
          asm volatile("cp.async.bulk.wait_group.read 1;" ::: "memory");
        }
        __syncwarp();
        if (p < 6) nb_arrive(nb_se((p + 1) & 1), 160);
        if (tid2 == 128) asm volatile("cp.async.bulk.wait_group.read 0;" ::: "memory");
        __syncwarp();
        if (p < 5) nb_arrive(NB_GO + (p & 1), 160);
      }
    }
    if (tid2 == 128) PROF(7);
  } else {
    asm volatile("setmaxnreg.inc.sync.aligned.u32 192;");
    ROLE_IDS();
    const int w = __shfl_sync(0xffffffffu, (tid >> 7) & 1, 0);
    const uint32_t li = lane & 7, lm = lane >> 3;
    {
      float acc[160];
#pragma unroll
      for (int i = 0; i < 160; i++) acc[i] = 0.f;
      reg_fence<160>(acc);
      if (tid == 256) PROF(1);
      uint32_t st = 2, ph = 0, pst = 0, ok = 0;
#pragma unroll 1
      for (int t = 0; t < 28; t++) {
        if (!ok) mbar_wait(sb + BAR_WFULL + 8 * st, ph);
        const uint32_t nst = (st == 5) ? 0 : st + 1, nph = (nst == 2) ? ph ^ 1 : ph;
        ok = mbar_test(sb + BAR_WFULL + 8 * nst, nph);
        const uint32_t da = dlo(sb + OFF_W) + st * (WST_B >> 4) + w * (8192 >> 4);
        const uint32_t db = dlo(sb + OFF_Q) + (((t >> 2) * 10240 + (t & 3) * 32) >> 4);
        wg_fence();
        static_for<0, 4>([&](auto C) { constexpr int cc = decltype(C)::value; wgmma_n80_mk1<cc * 2048, 0>(acc + 40 * cc, da, db); });
        wg_commit();
        wg_wait<1>();
        if (t > 0 && lane == 0) mbar_arrive(sb + BAR_WEMPT + 8 * pst);
        pst = st;
        st = nst;
        ph = nph;
      }
      wg_wait<0>();
      reg_fence<160>(acc);
      nb_sync(NB_O, 256);
      if (tid == 256) PROF(2);
      const uint32_t qa = sb + OFF_Q + (80 * w + 8 * (lm >> 1) + li) * 128 + (((2 * wi + (lm & 1)) ^ li) << 4);
#pragma unroll
      for (int cc = 0; cc < 4; cc++)
#pragma unroll
        for (int jj = 0; jj < 5; jj++) {
          const float* q = acc + 40 * cc + 8 * jj;
          stsm4t(qa + cc * QCHUNK + jj * 2048, pack_bf16(q[0], q[1]), pack_bf16(q[2], q[3]), pack_bf16(q[4], q[5]),
                 pack_bf16(q[6], q[7]));
        }
      fence_async();
      nb_arrive(NB_Q, 384);
    }
    {
    float acc[160];
#pragma unroll
    for (int i = 0; i < 160; i++) acc[i] = 0.f;
    reg_fence<160>(acc);
#pragma unroll 1
    for (int j = 0; j < 16; j++) {
      const uint32_t pb = j & 1;
      nb_sync(NB_PFULL + pb, 384);
      if (j > 0) {
        const float4 f = lds128(sb + OFF_FLAG + pb * 16);
        if ((__float_as_uint(f.x) | __float_as_uint(f.y) | __float_as_uint(f.z) | __float_as_uint(f.w)) != 0) {
          const uint32_t sc = sb + OFF_SC + pb * 640 + (lane & 3) * 160;
#pragma unroll
          for (int g = 0; g < 10; g++) {
            const float4 a = lds128(sc + g * 16);
#pragma unroll
            for (int mb = 0; mb < 2; mb++) {
              float* q = acc + 80 * mb + 8 * g;
              q[0] *= a.x; q[1] *= a.y; q[2] *= a.x; q[3] *= a.y;
              q[4] *= a.z; q[5] *= a.w; q[6] *= a.z; q[7] *= a.w;
            }
          }
        }
      }
      uint32_t slot, use;
      kv_slot(j == 15 ? 31 : 2 * j + 2, slot, use);
      reg_fence<160>(acc);
      if (j < 15) nb_sync(NB_GO + w, 256);
      else if (w == 1) nb_sync(NB_O, 256);
      if (j == 15 && w == 0) mbar_wait(sb + BAR_VL, 0);
      else mbar_wait(sb + BAR_FULL + 8 * slot, use & 1);
      if (tid == 256) PROF(24 + j);
      const uint32_t da = dlo(sb + OFF_SLOT) + slot * (SLOT_B >> 4) + w * (16384 >> 4);
      const uint32_t db = dlo(sb + OFF_P) + pb * (QCHUNK >> 4);
      wg_fence();
      static_for<0, 4>([&](auto K) {
        constexpr int ks = decltype(K)::value;
        wgmma_n160_mk1<ks * 2048, ks * 32>(acc, da, db);
        wgmma_n160_mk1<8192 + ks * 2048, ks * 32>(acc + 80, da, db);
      });
      wg_commit();
      if (j == 15 && w == 0) nb_arrive(NB_O, 256);
      wg_wait<0>();
      reg_fence<160>(acc);
      if (lane == 0) mbar_arrive(sb + BAR_EMPTY + 8 * slot);
      if (j < 14) nb_arrive(NB_PEMPTY + pb, 384);
    }
    if (tid == 256) PROF(4);
    {
      const uint32_t oa = sb + OFF_Q + 2 * w * QCHUNK + (8 * (lm >> 1) + li) * 128 + (((2 * wi + (lm & 1)) ^ li) << 4);
#pragma unroll
      for (int mb = 0; mb < 2; mb++)
#pragma unroll
        for (int jj = 0; jj < 10; jj++) {
          const float* q = acc + 80 * mb + 8 * jj;
          stsm4t(oa + mb * QCHUNK + jj * 2048, pack_bf16(q[0], q[1]), pack_bf16(q[2], q[3]), pack_bf16(q[4], q[5]),
                 pack_bf16(q[6], q[7]));
        }
      fence_async();
    }
    }
    nb_sync(NB_O2, 384);
    if (tid == 256) PROF(5);
    constexpr uint32_t dob = dlo(sb + OFF_Q);
    const uint32_t sta = sb + OFF_ST + (8 * (lm >> 1) + li) * 128 + (((2 * wi + (lm & 1)) ^ li) << 4);
    float linv[40];
#pragma unroll
    for (int g = 0; g < 10; g++) {
      const float4 f = lds128(sb + OFF_LINV + (lane & 3) * 160 + g * 16);
      linv[4 * g] = f.x; linv[4 * g + 1] = f.y; linv[4 * g + 2] = f.z; linv[4 * g + 3] = f.w;
    }
#pragma unroll 1
    for (int p = w; p < 7; p += 2) {
      float acc[40], acc1[40];
      uint32_t slot0, use0, slot1, use1;
      wo_slot(2 * p, slot0, use0);
      wo_slot(2 * p + 1, slot1, use1);
      mbar_wait(sb + BAR_FULL + 8 * slot0, use0 & 1);
      if (p > 0) nb_sync(NB_ORD + w, 256);
      if (lane == 0 && wi == 0) PT(40 + p);
      uint32_t da = dlo(sb + OFF_SLOT) + slot0 * (SLOT_B >> 4);
      wg_fence();
      wgmma_n80_mk_z<0, 0>(acc, da, dob);
      static_for<1, 9>([&](auto K) {
        constexpr int ks = decltype(K)::value;
        wgmma_n80_mk1<ks * 2048, (ks >> 2) * QCHUNK + (ks & 3) * 32>(acc, da, dob);
      });
      const uint32_t ok1 = mbar_test(sb + BAR_FULL + 8 * slot1, use1 & 1);
      static_for<9, 16>([&](auto K) {
        constexpr int ks = decltype(K)::value;
        wgmma_n80_mk1<ks * 2048, (ks >> 2) * QCHUNK + (ks & 3) * 32>(acc, da, dob);
      });
      wg_commit();
      if (!ok1) mbar_wait(sb + BAR_FULL + 8 * slot1, use1 & 1);
      da = dlo(sb + OFF_SLOT) + slot1 * (SLOT_B >> 4);
      wg_fence();
      wgmma_n80_mk_z<0, 10240>(acc1, da, dob);
      static_for<1, 6>([&](auto K) {
        constexpr int ks = decltype(K)::value;
        wgmma_n80_mk1<ks * 2048, 10240 + (ks >> 2) * QCHUNK + (ks & 3) * 32>(acc1, da, dob);
      });
      wg_commit();
      wg_wait<1>();
      if (lane == 0) mbar_arrive_n(sb + BAR_EMPTY + 8 * slot0, 2);
      wg_fence();
      static_for<6, 16>([&](auto K) {
        constexpr int ks = decltype(K)::value;
        wgmma_n80_mk1<ks * 2048, 10240 + (ks >> 2) * QCHUNK + (ks & 3) * 32>(acc1, da, dob);
      });
      wg_commit();
      if (p < 6) nb_arrive(NB_ORD + (w ^ 1), 256);
      wg_wait<0>();
      reg_fence<40>(acc);
      reg_fence<40>(acc1);
      if (lane == 0) mbar_arrive_n(sb + BAR_EMPTY + 8 * slot1, 2);
#pragma unroll
      for (int i = 0; i < 40; i++)
        acc[i] = fmaf(acc[i], linv[2 * (i >> 2) + (i & 1)], acc1[i] * linv[20 + 2 * (i >> 2) + (i & 1)]);
      uint32_t pk[20];
#pragma unroll
      for (int i = 0; i < 20; i++) pk[i] = pack_bf16(acc[2 * i], acc[2 * i + 1]);
      if (p > 1) nb_sync(NB_GO + w, 160);
#pragma unroll
      for (int k = 0; k < 4; k++) stsm4t(sta + w * 8192 + k * 2048, pk[4 * k], pk[4 * k + 1], pk[4 * k + 2], pk[4 * k + 3]);
      if (p > 0) nb_sync(nb_se(w), 160);
      stsm4t(sta + 16384, pk[16], pk[17], pk[18], pk[19]);
      fence_async();
      nb_arrive(NB_SF + w, 160);
      if (lane == 0 && wi == 0) PT(47 + p);
    }
    if (tid == 256) PROF(6);
    if (lane == 0 && wi == 0) PT(60 - w);
  }
}

typedef CUresult (*EncodeFn)(CUtensorMap*, CUtensorMapDataType, cuuint32_t, void*, const cuuint64_t*, const cuuint64_t*,
                             const cuuint32_t*, const cuuint32_t*, CUtensorMapInterleave, CUtensorMapSwizzle,
                             CUtensorMapL2promotion, CUtensorMapFloatOOBfill);

void encode3d(EncodeFn enc, CUtensorMap* m, void* p, uint64_t rows, uint64_t cols, uint32_t box_rows,
              uint32_t box_blocks) {
  cuuint64_t dims[3] = {64, rows, cols / 64};
  cuuint64_t strides[2] = {cols * 2, 128};
  cuuint32_t box[3] = {64, box_rows, box_blocks};
  cuuint32_t es[3] = {1, 1, 1};
  enc(m, CU_TENSOR_MAP_DATA_TYPE_BFLOAT16, 3, p, dims, strides, box, es, CU_TENSOR_MAP_INTERLEAVE_NONE,
      CU_TENSOR_MAP_SWIZZLE_128B, CU_TENSOR_MAP_L2_PROMOTION_L2_256B, CU_TENSOR_MAP_FLOAT_OOB_FILL_NONE);
}

}

extern "C" void kernel_launch(void* const* d_in, const int* in_sizes, int n_in, void* d_out, int out_size) {
  static EncodeFn enc = nullptr;
  if (!enc) {
    void* fn = nullptr;
    cudaDriverEntryPointQueryResult qr;
    cudaGetDriverEntryPoint("cuTensorMapEncodeTiled", &fn, cudaEnableDefault, &qr);
    enc = (EncodeFn)fn;
    cudaFuncSetAttribute(fused_gqa_kernel, cudaFuncAttributeMaxDynamicSharedMemorySize, SMEM_BYTES);
  }
  Maps maps;
  for (int blk = 0; blk < 2; blk++) {
    encode3d(enc, &maps.m[blk * 5 + 0], d_in[blk * 5 + 0], 640, 448, 80, 1);
    encode3d(enc, &maps.m[blk * 5 + 1], d_in[blk * 5 + 1], 65536, 256, 64, 4);
    encode3d(enc, &maps.m[blk * 5 + 2], d_in[blk * 5 + 2], 65536, 256, 64, 4);
    encode3d(enc, &maps.m[blk * 5 + 3], d_in[blk * 5 + 3], 448, 4096, 16, 8);
    encode3d(enc, &maps.m[blk * 5 + 4], d_in[blk * 5 + 4], 4096, 448, 256, 1);
    encode3d(enc, &maps.k8[blk], d_in[blk * 5 + 1], 65536, 256, 64, 1);
    encode3d(enc, &maps.v16[blk], d_in[blk * 5 + 2], 65536, 256, 64, 2);
  }
  encode3d(enc, &maps.o, d_out, 640, 896, 16, 1);
  fused_gqa_kernel<<<NCTA, NTHREADS, SMEM_BYTES>>>(maps, (__nv_bfloat16*)d_out);
}
```

```cpp
#include <cuda_runtime.h>
#include <cuda_bf16.h>
#include <cuda.h>
#include <stdint.h>

namespace {

constexpr int NCTA = 128;
constexpr int NTHREADS = 512;

constexpr uint32_t SB = 0x400;
constexpr uint32_t OFF_Q     = 0;
constexpr uint32_t QCHUNK    = 20480;
constexpr uint32_t OFF_SLOT  = 81920;
constexpr uint32_t SLOT_B    = 32768;
constexpr uint32_t OFF_P     = OFF_SLOT + 3 * SLOT_B;
constexpr uint32_t OFF_W     = OFF_SLOT + SLOT_B;
constexpr uint32_t WST_B     = 16384;
constexpr uint32_t OFF_SC    = OFF_P + 2 * QCHUNK;
constexpr uint32_t OFF_FLAG  = OFF_SC + 1280;
constexpr uint32_t OFF_LINV  = OFF_FLAG + 32;
constexpr uint32_t OFF_ST    = OFF_P + SLOT_B;
constexpr uint32_t OFF_BAR   = OFF_ST + 18432;
constexpr uint32_t BAR_FULL  = OFF_BAR;
constexpr uint32_t BAR_EMPTY = BAR_FULL + 32;
constexpr uint32_t BAR_WFULL = BAR_EMPTY + 32;
constexpr uint32_t BAR_WEMPT = BAR_WFULL + 48;
constexpr uint32_t BAR_T     = BAR_WEMPT + 48;
constexpr uint32_t BAR_VL    = BAR_T + 8;
constexpr uint32_t OFF_MISC  = BAR_VL + 8;
constexpr uint32_t OFF_PROF  = OFF_MISC + 16;
constexpr uint32_t SMEM_USED = OFF_PROF + 256;
constexpr uint32_t SMEM_BYTES = SMEM_USED;

#define PACE_TAU 1350
#define PACE_T0 3400
#define PACE_MIN 1250

struct Maps {
  CUtensorMap m[10];
  CUtensorMap k8[2];
  CUtensorMap v16[2];
  CUtensorMap o;
};

__device__ unsigned int g_zero[16 * 32];
#define PT(idx) do {} while (0)
#define PROF(idx) do {} while (0)

__device__ __forceinline__ void mbar_init(uint32_t bar, uint32_t cnt) {
  asm volatile("mbarrier.init.shared::cta.b64 [%0], %1;" ::"r"(bar), "r"(cnt) : "memory");
}
__device__ __forceinline__ void mbar_expect_tx(uint32_t bar, uint32_t bytes) {
  asm volatile("mbarrier.arrive.expect_tx.shared::cta.b64 _, [%0], %1;" ::"r"(bar), "r"(bytes) : "memory");
}
__device__ __forceinline__ void mbar_arrive(uint32_t bar) {
  asm volatile("mbarrier.arrive.shared::cta.b64 _, [%0];" ::"r"(bar) : "memory");
}
__device__ __forceinline__ void mbar_arrive_n(uint32_t bar, uint32_t n) {
  asm volatile("mbarrier.arrive.shared::cta.b64 _, [%0], %1;" ::"r"(bar), "r"(n) : "memory");
}
__device__ __forceinline__ void mbar_wait(uint32_t bar, uint32_t parity) {
  asm volatile(
      "{\n.reg .pred p;\n.reg .u32 c;\nmov.u32 c, 0;\n"
      "W_LOOP:\n"
      "mbarrier.try_wait.parity.shared::cta.b64 p, [%0], %1;\n"
      "@p bra W_DONE;\n"
      "add.u32 c, c, 1;\n"
      "setp.lt.u32 p, c, 0x400000;\n"
      "@p bra W_LOOP;\n"
      "trap;\n"
      "W_DONE:\n}\n" ::"r"(bar), "r"(parity) : "memory");
}
__device__ __forceinline__ uint32_t mbar_test(uint32_t bar, uint32_t parity) {
  uint32_t ok;
  asm volatile("{\n.reg .pred p;\nmbarrier.test_wait.parity.shared::cta.b64 p, [%1], %2;\nselp.u32 %0, 1, 0, p;\n}\n"
               : "=r"(ok) : "r"(bar), "r"(parity) : "memory");
  return ok;
}
__device__ __forceinline__ void nb_sync(uint32_t id, uint32_t n) { asm volatile("bar.sync %0, %1;" ::"r"(id), "r"(n) : "memory"); }
__device__ __forceinline__ void nb_arrive(uint32_t id, uint32_t n) { asm volatile("bar.arrive %0, %1;" ::"r"(id), "r"(n) : "memory"); }
constexpr uint32_t NB_O = 1, NB_PFULL = 2, NB_PEMPTY = 4, NB_GO = 6, NB_Q = 8, NB_ORD = 10, NB_O2 = 12, NB_S = 13, NB_SF = 14;
__device__ __forceinline__ uint32_t nb_se(uint32_t w) { return w ? NB_S : NB_Q; }
__device__ __forceinline__ void tma3d(uint32_t dst, const CUtensorMap* m, int c1, int c2, uint32_t bar) {
  asm volatile(
      "cp.async.bulk.tensor.3d.shared::cluster.global.mbarrier::complete_tx::bytes [%0], [%1, {%2, %3, %4}], [%5];"
      ::"r"(dst), "l"(m), "r"(0), "r"(c1), "r"(c2), "r"(bar) : "memory");
}
__device__ __forceinline__ void tma3d_ef(uint32_t dst, const CUtensorMap* m, int c1, int c2, uint32_t bar, uint64_t pol) {
  asm volatile(
      "cp.async.bulk.tensor.3d.shared::cluster.global.mbarrier::complete_tx::bytes.L2::cache_hint [%0], [%1, {%2, %3, %4}], [%5], %6;"
      ::"r"(dst), "l"(m), "r"(0), "r"(c1), "r"(c2), "r"(bar), "l"(pol) : "memory");
}
__device__ __forceinline__ void tma3d_pf(const CUtensorMap* m, int c1, int c2) {
  asm volatile("cp.async.bulk.prefetch.tensor.3d.L2.global [%0, {%1, %2, %3}];" ::"l"(m), "r"(0), "r"(c1), "r"(c2)
               : "memory");
}
__device__ __forceinline__ void wg_fence() { asm volatile("wgmma.fence.sync.aligned;" ::: "memory"); }
__device__ __forceinline__ void wg_commit() { asm volatile("wgmma.commit_group.sync.aligned;" ::: "memory"); }
template <int N>
__device__ __forceinline__ void wg_wait() { asm volatile("wgmma.wait_group.sync.aligned %0;" ::"n"(N) : "memory"); }
__device__ __forceinline__ void fence_async() { asm volatile("fence.proxy.async.shared::cta;" ::: "memory"); }
template <int N>
__device__ __forceinline__ void reg_fence(float* d) {
#pragma unroll
  for (int i = 0; i < N; i++) asm volatile("" : "+f"(d[i])::"memory");
}
__device__ __forceinline__ constexpr uint32_t dlo(uint32_t saddr) { return ((saddr & 0x3FFFFu) >> 4) | (1u << 16); }
template <int V>
struct IC { static constexpr int value = V; };
template <int I, int N, class F>
__device__ __forceinline__ void static_for(F&& f) {
  if constexpr (I < N) {
    f(IC<I>{});
    static_for<I + 1, N>(f);
  }
}
__device__ __forceinline__ uint32_t pack_bf16(float lo, float hi) {
  uint32_t r;
  asm("cvt.rn.bf16x2.f32 %0, %1, %2;" : "=r"(r) : "f"(hi), "f"(lo));
  return r;
}
template <uint32_t XR, uint32_t OFF>
__device__ __forceinline__ void stsm4_o(uint32_t a, uint32_t r0, uint32_t r1, uint32_t r2, uint32_t r3) {
  asm volatile("{\n.reg .b32 t;\nxor.b32 t, %0, %6;\nstmatrix.sync.aligned.m8n8.x4.shared.b16 [t + %5], {%1, %2, %3, %4};\n}\n"
               ::"r"(a), "r"(r0), "r"(r1), "r"(r2), "r"(r3), "n"(OFF), "n"(XR) : "memory");
}
__device__ __forceinline__ void stsm4t(uint32_t a, uint32_t r0, uint32_t r1, uint32_t r2, uint32_t r3) {
  asm volatile("stmatrix.sync.aligned.m8n8.x4.trans.shared.b16 [%0], {%1, %2, %3, %4};" ::"r"(a), "r"(r0), "r"(r1),
               "r"(r2), "r"(r3) : "memory");
}
__device__ __forceinline__ float ex2(float x) {
  float y;
  asm("ex2.approx.ftz.f32 %0, %1;" : "=f"(y) : "f"(x));
  return y;
}
__device__ __forceinline__ float4 lds128(uint32_t a) {
  float4 v;
  asm volatile("ld.shared.v4.f32 {%0, %1, %2, %3}, [%4];" : "=f"(v.x), "=f"(v.y), "=f"(v.z), "=f"(v.w) : "r"(a) : "memory");
  return v;
}
__device__ __forceinline__ void sts32(uint32_t a, float v) {
  asm volatile("st.shared.f32 [%0], %1;" ::"r"(a), "f"(v) : "memory");
}
template <uint32_t OA, uint32_t OB, uint32_t HIA = 0x40000040u>
__device__ __forceinline__ void wgmma_n64_kk_z(float* d, uint32_t a, uint32_t b) {
  asm volatile(
      "{\n.reg .b32 ta, tb;\n.reg .b64 da, db;\nadd.u32 ta, %32, %34;\nadd.u32 tb, %33, %35;\nmov.b64 da, {ta, %36};\nmov.b64 db, {tb, 0x40000040};\n"
      "wgmma.mma_async.sync.aligned.m64n64k16.f32.bf16.bf16 {"
      "%0, %1, %2, %3, %4, %5, %6, %7, %8, %9, %10, %11, %12, %13, %14, %15,"
      "%16, %17, %18, %19, %20, %21, %22, %23, %24, %25, %26, %27, %28, %29, %30, %31}, da, db, 0, 1, 1, 0, 0;\n}\n"
      : "=f"(d[0]), "=f"(d[1]), "=f"(d[2]), "=f"(d[3]), "=f"(d[4]), "=f"(d[5]), "=f"(d[6]), "=f"(d[7]),
        "=f"(d[8]), "=f"(d[9]), "=f"(d[10]), "=f"(d[11]), "=f"(d[12]), "=f"(d[13]), "=f"(d[14]), "=f"(d[15]),
        "=f"(d[16]), "=f"(d[17]), "=f"(d[18]), "=f"(d[19]), "=f"(d[20]), "=f"(d[21]), "=f"(d[22]), "=f"(d[23]),
        "=f"(d[24]), "=f"(d[25]), "=f"(d[26]), "=f"(d[27]), "=f"(d[28]), "=f"(d[29]), "=f"(d[30]), "=f"(d[31])
      : "r"(a), "r"(b), "n"(OA >> 4), "n"(OB >> 4), "n"(HIA));
}

template <uint32_t OA, uint32_t OB, uint32_t HIA = 0x40000040u>
__device__ __forceinline__ void wgmma_n64_kk(float* d, uint32_t a, uint32_t b) {
  asm volatile(
      "{\n.reg .b32 ta, tb;\n.reg .b64 da, db;\nadd.u32 ta, %32, %34;\nadd.u32 tb, %33, %35;\nmov.b64 da, {ta, %36};\nmov.b64 db, {tb, 0x40000040};\n"
      "wgmma.mma_async.sync.aligned.m64n64k16.f32.bf16.bf16 {"
      "%0, %1, %2, %3, %4, %5, %6, %7, %8, %9, %10, %11, %12, %13, %14, %15,"
      "%16, %17, %18, %19, %20, %21, %22, %23, %24, %25, %26, %27, %28, %29, %30, %31}, da, db, 1, 1, 1, 0, 0;\n}\n"
      : "+f"(d[0]), "+f"(d[1]), "+f"(d[2]), "+f"(d[3]), "+f"(d[4]), "+f"(d[5]), "+f"(d[6]), "+f"(d[7]),
        "+f"(d[8]), "+f"(d[9]), "+f"(d[10]), "+f"(d[11]), "+f"(d[12]), "+f"(d[13]), "+f"(d[14]), "+f"(d[15]),
        "+f"(d[16]), "+f"(d[17]), "+f"(d[18]), "+f"(d[19]), "+f"(d[20]), "+f"(d[21]), "+f"(d[22]), "+f"(d[23]),
        "+f"(d[24]), "+f"(d[25]), "+f"(d[26]), "+f"(d[27]), "+f"(d[28]), "+f"(d[29]), "+f"(d[30]), "+f"(d[31])
      : "r"(a), "r"(b), "n"(OA >> 4), "n"(OB >> 4), "n"(HIA));
}

template <uint32_t OA, uint32_t OB, uint32_t HIA = 0x40000040u>
__device__ __forceinline__ void wgmma_n80_mk_z(float* d, uint32_t a, uint32_t b) {
  asm volatile(
      "{\n.reg .b32 ta, tb;\n.reg .b64 da, db;\nadd.u32 ta, %40, %42;\nadd.u32 tb, %41, %43;\nmov.b64 da, {ta, %44};\nmov.b64 db, {tb, 0x40000040};\n"
      "wgmma.mma_async.sync.aligned.m64n80k16.f32.bf16.bf16 {"
      "%0, %1, %2, %3, %4, %5, %6, %7, %8, %9, %10, %11, %12, %13, %14, %15,"
      "%16, %17, %18, %19, %20, %21, %22, %23, %24, %25, %26, %27, %28, %29, %30, %31,"
      "%32, %33, %34, %35, %36, %37, %38, %39}, da, db, 0, 1, 1, 1, 0;\n}\n"
      : "=f"(d[0]), "=f"(d[1]), "=f"(d[2]), "=f"(d[3]), "=f"(d[4]), "=f"(d[5]), "=f"(d[6]), "=f"(d[7]),
        "=f"(d[8]), "=f"(d[9]), "=f"(d[10]), "=f"(d[11]), "=f"(d[12]), "=f"(d[13]), "=f"(d[14]), "=f"(d[15]),
        "=f"(d[16]), "=f"(d[17]), "=f"(d[18]), "=f"(d[19]), "=f"(d[20]), "=f"(d[21]), "=f"(d[22]), "=f"(d[23]),
        "=f"(d[24]), "=f"(d[25]), "=f"(d[26]), "=f"(d[27]), "=f"(d[28]), "=f"(d[29]), "=f"(d[30]), "=f"(d[31]),
        "=f"(d[32]), "=f"(d[33]), "=f"(d[34]), "=f"(d[35]), "=f"(d[36]), "=f"(d[37]), "=f"(d[38]), "=f"(d[39])
      : "r"(a), "r"(b), "n"(OA >> 4), "n"(OB >> 4), "n"(HIA));
}

template <uint32_t OA, uint32_t OB, uint32_t HIA = 0x40000040u>
__device__ __forceinline__ void wgmma_n80_mk1(float* d, uint32_t a, uint32_t b) {
  asm volatile(
      "{\n.reg .b32 ta, tb;\n.reg .b64 da, db;\nadd.u32 ta, %40, %42;\nadd.u32 tb, %41, %43;\nmov.b64 da, {ta, %44};\nmov.b64 db, {tb, 0x40000040};\n"
      "wgmma.mma_async.sync.aligned.m64n80k16.f32.bf16.bf16 {"
      "%0, %1, %2, %3, %4, %5, %6, %7, %8, %9, %10, %11, %12, %13, %14, %15,"
      "%16, %17, %18, %19, %20, %21, %22, %23, %24, %25, %26, %27, %28, %29, %30, %31,"
      "%32, %33, %34, %35, %36, %37, %38, %39}, da, db, 1, 1, 1, 1, 0;\n}\n"
      : "+f"(d[0]), "+f"(d[1]), "+f"(d[2]), "+f"(d[3]), "+f"(d[4]), "+f"(d[5]), "+f"(d[6]), "+f"(d[7]),
        "+f"(d[8]), "+f"(d[9]), "+f"(d[10]), "+f"(d[11]), "+f"(d[12]), "+f"(d[13]), "+f"(d[14]), "+f"(d[15]),
        "+f"(d[16]), "+f"(d[17]), "+f"(d[18]), "+f"(d[19]), "+f"(d[20]), "+f"(d[21]), "+f"(d[22]), "+f"(d[23]),
        "+f"(d[24]), "+f"(d[25]), "+f"(d[26]), "+f"(d[27]), "+f"(d[28]), "+f"(d[29]), "+f"(d[30]), "+f"(d[31]),
        "+f"(d[32]), "+f"(d[33]), "+f"(d[34]), "+f"(d[35]), "+f"(d[36]), "+f"(d[37]), "+f"(d[38]), "+f"(d[39])
      : "r"(a), "r"(b), "n"(OA >> 4), "n"(OB >> 4), "n"(HIA));
}

template <uint32_t OA, uint32_t OB, uint32_t HIA = 0x40000040u>
__device__ __forceinline__ void wgmma_n160_mk1(float* d, uint32_t a, uint32_t b) {
  asm volatile(
      "{\n.reg .b32 ta, tb;\n.reg .b64 da, db;\nadd.u32 ta, %80, %82;\nadd.u32 tb, %81, %83;\nmov.b64 da, {ta, %84};\nmov.b64 db, {tb, 0x40000040};\n"
      "wgmma.mma_async.sync.aligned.m64n160k16.f32.bf16.bf16 {"
      "%0, %1, %2, %3, %4, %5, %6, %7, %8, %9, %10, %11, %12, %13, %14, %15,"
      "%16, %17, %18, %19, %20, %21, %22, %23, %24, %25, %26, %27, %28, %29, %30, %31,"
      "%32, %33, %34, %35, %36, %37, %38, %39, %40, %41, %42, %43, %44, %45, %46, %47,"
      "%48, %49, %50, %51, %52, %53, %54, %55, %56, %57, %58, %59, %60, %61, %62, %63,"
      "%64, %65, %66, %67, %68, %69, %70, %71, %72, %73, %74, %75, %76, %77, %78, %79}, da, db, 1, 1, 1, 1, 0;\n}\n"
      : "+f"(d[0]), "+f"(d[1]), "+f"(d[2]), "+f"(d[3]), "+f"(d[4]), "+f"(d[5]), "+f"(d[6]), "+f"(d[7]),
        "+f"(d[8]), "+f"(d[9]), "+f"(d[10]), "+f"(d[11]), "+f"(d[12]), "+f"(d[13]), "+f"(d[14]), "+f"(d[15]),
        "+f"(d[16]), "+f"(d[17]), "+f"(d[18]), "+f"(d[19]), "+f"(d[20]), "+f"(d[21]), "+f"(d[22]), "+f"(d[23]),
        "+f"(d[24]), "+f"(d[25]), "+f"(d[26]), "+f"(d[27]), "+f"(d[28]), "+f"(d[29]), "+f"(d[30]), "+f"(d[31]),
        "+f"(d[32]), "+f"(d[33]), "+f"(d[34]), "+f"(d[35]), "+f"(d[36]), "+f"(d[37]), "+f"(d[38]), "+f"(d[39]),
        "+f"(d[40]), "+f"(d[41]), "+f"(d[42]), "+f"(d[43]), "+f"(d[44]), "+f"(d[45]), "+f"(d[46]), "+f"(d[47]),
        "+f"(d[48]), "+f"(d[49]), "+f"(d[50]), "+f"(d[51]), "+f"(d[52]), "+f"(d[53]), "+f"(d[54]), "+f"(d[55]),
        "+f"(d[56]), "+f"(d[57]), "+f"(d[58]), "+f"(d[59]), "+f"(d[60]), "+f"(d[61]), "+f"(d[62]), "+f"(d[63]),
        "+f"(d[64]), "+f"(d[65]), "+f"(d[66]), "+f"(d[67]), "+f"(d[68]), "+f"(d[69]), "+f"(d[70]), "+f"(d[71]),
        "+f"(d[72]), "+f"(d[73]), "+f"(d[74]), "+f"(d[75]), "+f"(d[76]), "+f"(d[77]), "+f"(d[78]), "+f"(d[79])
      : "r"(a), "r"(b), "n"(OA >> 4), "n"(OB >> 4), "n"(HIA));
}

__device__ __forceinline__ void kv_slot(int i, uint32_t& slot, uint32_t& use) {
  use = (uint32_t)i / 3u;
  slot = (uint32_t)i - use * 3u;
}
__device__ __forceinline__ void wo_slot(int u, uint32_t& slot, uint32_t& use) {
  uint32_t r = u & 3, q = u >> 2;
  slot = (r == 0) ? 2u : (r == 3) ? 3u : (r - 1u);
  use = q + ((r == 0) ? 10u : (r == 3) ? 0u : 11u);
}

struct SCtx {
  uint32_t pa01, pa2, sa01, sa2;
  bool wr;
};

template <int BLK>
__device__ __forceinline__ void qk_issue(float* s, uint32_t dk) {
  constexpr uint32_t dq = dlo(SB + OFF_Q + BLK * 8192);
  constexpr uint32_t HI = (BLK == 2) ? 0x40000020u : 0x40000040u;
  wg_fence();
  constexpr uint32_t T = BLK << 20;
  wgmma_n64_kk_z<0, T, HI>(s, dq, dk);
  static_for<1, 16>([&](auto I) {
    constexpr int ks = decltype(I)::value;
    wgmma_n64_kk<(ks >> 2) * QCHUNK + (ks & 3) * 32, T + (ks >> 2) * 8192 + (ks & 3) * 32, HI>(s, dq, dk);
  });
  wg_commit();
}

template <int BLK, class F>
__device__ __forceinline__ void softmax_blk(float* s, float* mc, float* l, uint32_t& flag, const SCtx& cx, F&& mid) {
  constexpr float c = 0.0625f * 1.4426950408889634f;
  constexpr int NR = (BLK == 2) ? 1 : 2;
  float mx[NR], alpha[NR];
  bool need = false;
#pragma unroll
  for (int r = 0; r < NR; r++) {
    float v0 = fmaxf(s[2 * r], s[2 * r + 1]), v1 = fmaxf(s[2 * r + 4], s[2 * r + 5]);
#pragma unroll
    for (int g = 2; g < 8; g += 2) {
      v0 = fmaxf(v0, fmaxf(s[2 * r + 4 * g], s[2 * r + 4 * g + 1]));
      v1 = fmaxf(v1, fmaxf(s[2 * r + 4 * g + 4], s[2 * r + 4 * g + 5]));
    }
    mx[r] = fmaxf(v0, v1) * c;
    need |= !(mx[r] - mc[2 * BLK + r] <= 8.f);
    alpha[r] = 1.f;
  }
  if (__any_sync(0xffffffffu, need)) {
#pragma unroll
    for (int r = 0; r < NR; r++) mx[r] = fmaxf(mx[r], __shfl_xor_sync(0xffffffffu, mx[r], 1));
#pragma unroll
    for (int r = 0; r < NR; r++) mx[r] = fmaxf(mx[r], __shfl_xor_sync(0xffffffffu, mx[r], 2));
#pragma unroll
    for (int r = 0; r < NR; r++) {
      const float mo = mc[2 * BLK + r];
      const float mn = fmaxf(mo, mx[r]);
      alpha[r] = ex2(mo - mn);
      mc[2 * BLK + r] = mn;
      l[2 * BLK + r] *= alpha[r];
    }
    flag = 1;
  }
#pragma unroll
  for (int r = 0; r < NR; r++) {
    const float nm = -mc[2 * BLK + r];
    float sum0 = l[2 * BLK + r], sum1 = 0.f;
#pragma unroll
    for (int g = 0; g < 8; g++) {
      const float p0 = ex2(fmaf(s[2 * r + 4 * g], c, nm));
      const float p1 = ex2(fmaf(s[2 * r + 4 * g + 1], c, nm));
      s[2 * r + 4 * g] = p0;
      s[2 * r + 4 * g + 1] = p1;
      sum0 += p0;
      sum1 += p1;
    }
    const float lr = sum0 + sum1;
    l[2 * BLK + r] = lr;
    alpha[r] = fmaf(lr, 0.f, alpha[r]);
    if (r == 0) mid();
  }
  if (BLK < 2) {
    static_for<0, 4>([&](auto G) {
      constexpr int g = decltype(G)::value;
      const float* q = s + g * 8;
      stsm4_o<(g << 5), BLK * 8192>(cx.pa01, pack_bf16(q[0], q[1]), pack_bf16(q[2], q[3]), pack_bf16(q[4], q[5]),
                                    pack_bf16(q[6], q[7]));
    });
    if (cx.wr) {
      sts32(cx.sa01 + BLK * 64, alpha[0]);
      sts32(cx.sa01 + BLK * 64 + 8, alpha[NR - 1]);
    }
  } else {
    static_for<0, 2>([&](auto G) {
      constexpr int g = decltype(G)::value;
      const float* q = s + g * 16;
      stsm4_o<(g << 6), 0>(cx.pa2, pack_bf16(q[0], q[1]), pack_bf16(q[4], q[5]), pack_bf16(q[8], q[9]),
                           pack_bf16(q[12], q[13]));
    });
    if (cx.wr) sts32(cx.sa2, alpha[0]);
  }
}

__device__ __forceinline__ void s_tile(int j, float* mc, float* l, SCtx& cx, int wi, int lane) {
  constexpr uint32_t sb = SB;
  float sX[32], sY[32];
  uint32_t flag = 0, slot, use;
  const uint32_t pb = j & 1;
  kv_slot(j == 0 ? 0 : 2 * j - 1, slot, use);
  mbar_wait(sb + BAR_FULL + 8 * slot, use & 1);
  if (wi == 0) PROF(8 + j);
  const uint32_t dk = dlo(sb + OFF_SLOT) + slot * (SLOT_B >> 4);
  qk_issue<0>(sX, dk);
  qk_issue<1>(sY, dk);
  if (j >= 2) nb_sync(NB_PEMPTY + pb, 384);
  if (j >= 1) nb_arrive(NB_GO, 256);
  wg_wait<1>();
  reg_fence<32>(sX);
  softmax_blk<0>(sX, mc, l, flag, cx, [] {});
  qk_issue<2>(sX, dk);
  if (j >= 1) nb_arrive(NB_GO + 1, 256);
  wg_wait<1>();
  reg_fence<32>(sY);
  softmax_blk<1>(sY, mc, l, flag, cx, [&] {
    wg_wait<0>();
    if (lane == 0) mbar_arrive_n(sb + BAR_EMPTY + 8 * slot, 2);
  });
  reg_fence<32>(sX);
  softmax_blk<2>(sX, mc, l, flag, cx, [] {});
  if (lane == 0) asm volatile("st.shared.u32 [%0], %1;" ::"r"(sb + OFF_FLAG + pb * 16 + wi * 4), "r"(flag) : "memory");
  fence_async();
  nb_arrive(NB_PFULL + pb, 384);
  const uint32_t dp = pb ? (0u - QCHUNK) : QCHUNK, ds = pb ? (0u - 640u) : 640u;
  cx.pa01 += dp; cx.pa2 += dp; cx.sa01 += ds; cx.sa2 += ds;
}

__global__ void __launch_bounds__(NTHREADS, 1)
fused_gqa_kernel(const __grid_constant__ Maps maps, __nv_bfloat16* __restrict__ out) {
  extern __shared__ uint8_t smem_raw[];
  constexpr uint32_t sb = SB;
  if ((uint32_t)__cvta_generic_to_shared(smem_raw) != sb) __trap();
  const int wg = __shfl_sync(0xffffffffu, threadIdx.x >> 7, 0);
#define ROLE_IDS()                                                   \
  int tid, bid;                                                      \
  asm volatile("mov.u32 %0, %%tid.x;" : "=r"(tid));                  \
  asm volatile("mov.u32 %0, %%ctaid.x;" : "=r"(bid));                \
  const int wi = __shfl_sync(0xffffffffu, (tid >> 5) & 3, 0);        \
  const int lane = tid & 31;                                         \
  const int blk = bid >> 6, kvh = (bid >> 3) & 7, b = bid & 7;       \
  (void)wi; (void)lane; (void)blk; (void)kvh; (void)b

  if (threadIdx.x == 0) {
    PROF(0);
    for (int s = 0; s < 4; s++) {
      mbar_init(sb + BAR_FULL + 8 * s, 1);
      mbar_init(sb + BAR_EMPTY + 8 * s, 8);
    }
    for (int s = 0; s < 6; s++) {
      mbar_init(sb + BAR_WFULL + 8 * s, 1);
      mbar_init(sb + BAR_WEMPT + 8 * s, 8);
    }
    mbar_init(sb + BAR_T, 1);
    mbar_init(sb + BAR_VL, 1);
    asm volatile("fence.mbarrier_init.release.cluster;" ::: "memory");
    fence_async();
  }
  if (threadIdx.x < 32) {
    nb_arrive(0, 480);
    nb_arrive(15, 64);
    if (threadIdx.x == 0) {
      const int blk = blockIdx.x >> 6, kvh = (blockIdx.x >> 3) & 7, b = blockIdx.x & 7;
      const CUtensorMap* mx0 = &maps.m[blk * 5 + 0];
      const CUtensorMap* mw0 = &maps.m[blk * 5 + 3];
      static_for<0, 2>([&](auto T) {
        constexpr int t = decltype(T)::value, st = (t + 2) % 6, xc = t ? t - 1 : 0;
        constexpr bool hx = (t == 0) || (xc >= 1);
        mbar_expect_tx(sb + BAR_WFULL + 8 * st, hx ? WST_B + 10240 : WST_B);
        if constexpr (t == 0) tma3d(sb + OFF_Q, mx0, b * 80, 0, sb + BAR_WFULL + 8 * st);
        tma3d(sb + OFF_W + st * WST_B, mw0, 16 * t, kvh * 8, sb + BAR_WFULL + 8 * st);
        if constexpr (t > 0 && hx) tma3d(sb + OFF_Q + xc * 10240, mx0, b * 80, xc, sb + BAR_WFULL + 8 * st);
      });
    }
    __syncwarp();
  }

  if (wg == 0) {
    asm volatile("setmaxnreg.dec.sync.aligned.u32 24;");
    ROLE_IDS();
    if (wi == 1) nb_sync(15, 64);
    if (wi > 1) nb_sync(0, 480);
    if (tid == 32) {
      const CUtensorMap* mx0 = &maps.m[blk * 5 + 0];
      const CUtensorMap* mw0 = &maps.m[blk * 5 + 3];
      static_for<2, 6>([&](auto T) {
        constexpr int t = decltype(T)::value, st = (t + 2) % 6, xc = t - 1;
        constexpr bool hx = (xc >= 1);
        mbar_expect_tx(sb + BAR_WFULL + 8 * st, hx ? WST_B + 10240 : WST_B);
        tma3d(sb + OFF_W + st * WST_B, mw0, 16 * t, kvh * 8, sb + BAR_WFULL + 8 * st);
        if constexpr (hx) tma3d(sb + OFF_Q + xc * 10240, mx0, b * 80, xc, sb + BAR_WFULL + 8 * st);
      });
    }
    if (tid >= 64 && tid < 70) {
      const CUtensorMap* m = (tid == 64) ? &maps.k8[blk] : (tid == 68) ? &maps.v16[blk] : (tid == 69) ? &maps.o
                                                         : &maps.m[blk * 5 + (tid == 65 ? 1 : tid == 66 ? 2 : 4)];
      asm volatile("prefetch.tensormap [%0];" ::"l"(m) : "memory");
    }
    if (wi == 3) {
      __nanosleep(20000);
      __nv_bfloat16* o = out + (size_t)(b * 80 + kvh * 10) * 896 + blk * 448;
#pragma unroll 1
      for (int r = 0; r < 10; r++) {
        *reinterpret_cast<uint4*>(o + r * 896 + lane * 8) = make_uint4(0, 0, 0, 0);
        if (lane < 24) *reinterpret_cast<uint4*>(o + r * 896 + 256 + lane * 8) = make_uint4(0, 0, 0, 0);
      }
      __threadfence();
      __syncwarp();
      if (lane == 0) {
        uint32_t old;
        asm volatile("atom.release.gpu.global.add.u32 %0, [%1], 1;" : "=r"(old) : "l"(g_zero + (blk * 8 + b) * 32) : "memory");
        asm volatile("st.shared.u32 [%0], %1;" ::"r"(sb + OFF_MISC), "r"((old | 7u) + 1u) : "memory");
        mbar_arrive(sb + BAR_T);
      }
    }
    if (tid == 0) {
      const CUtensorMap* mk = &maps.m[blk * 5 + 1];
      const CUtensorMap* mv = &maps.m[blk * 5 + 2];
      const CUtensorMap* mwq = &maps.m[blk * 5 + 3];
      const CUtensorMap* mwo = &maps.m[blk * 5 + 4];
      const int row0 = (b * 8 + kvh) * 1024;
      uint32_t tstart, t1 = 0, t2 = 0;
      asm volatile("mov.u32 %0, %%globaltimer_lo;" : "=r"(tstart));
      uint64_t pol;
      asm volatile("createpolicy.fractional.L2::evict_first.b64 %0, 1.0;" : "=l"(pol));
      const CUtensorMap* mx = &maps.m[blk * 5 + 0];
      uint32_t st = 2, ph = 0;
#pragma unroll 1
      for (int t = 6; t < 28; t++) {
        if (t == 6) tma3d_pf(mwq, 16 * (6 + b), kvh * 8);
        if (t == 10) tma3d_pf(mwq, 16 * (14 + b), kvh * 8);
        if (t == 14 && b < 6) tma3d_pf(mwq, 16 * (22 + b), kvh * 8);
        if (t >= 18 && t < 26 && !(t & 1)) {
          const int q = (t - 18) >> 1;
          if (q == 0) mbar_expect_tx(sb + BAR_FULL, SLOT_B);
          tma3d_ef(sb + OFF_SLOT + q * 8192, &maps.k8[blk], row0, q, sb + BAR_FULL, pol);
        }
        mbar_wait(sb + BAR_WEMPT + 8 * st, ph);
        const int xc = t - 1;
        const bool hx = xc < 7;
        mbar_expect_tx(sb + BAR_WFULL + 8 * st, hx ? WST_B + 10240 : WST_B);
        tma3d(sb + OFF_W + st * WST_B, mwq, 16 * t, kvh * 8, sb + BAR_WFULL + 8 * st);
        if (hx) tma3d(sb + OFF_Q + xc * 10240, mx, b * 80, xc, sb + BAR_WFULL + 8 * st);
        if (++st == 6) st = 0;
        if (st == 2) ph ^= 1;
      }
      mbar_wait(sb + BAR_WEMPT, 1);
      mbar_wait(sb + BAR_WEMPT + 8, 1);
      mbar_expect_tx(sb + BAR_FULL + 8, SLOT_B);
      tma3d_ef(sb + OFF_SLOT + SLOT_B, mk, row0 + 64, 0, sb + BAR_FULL + 8, pol);
      mbar_wait(sb + BAR_WEMPT + 16, 0);
      mbar_wait(sb + BAR_WEMPT + 24, 0);
#pragma unroll 1
      for (int i = 2; i < 32; i++) {
        uint32_t s, use;
        kv_slot(i, s, use);
        const bool isv = !(i & 1);
        const int j = isv ? ((i - 2) >> 1) : ((i + 1) >> 1);
        if (use > 0) mbar_wait(sb + BAR_EMPTY + 8 * s, (use - 1) & 1);
        {
          uint32_t due = PACE_T0 + i * PACE_TAU, now;
          if (i >= 8) due = max(due, t2 + 2 * PACE_MIN);
          do { asm volatile("mov.u32 %0, %%globaltimer_lo;" : "=r"(now)); } while (now - tstart < due);
          t2 = t1;
          t1 = now - tstart;
        }
        if (i == 31) {
          mbar_expect_tx(sb + BAR_VL, SLOT_B / 2);
          tma3d_ef(sb + OFF_SLOT + s * SLOT_B, &maps.v16[blk], row0 + 960, 0, sb + BAR_VL, pol);
          mbar_expect_tx(sb + BAR_FULL + 8 * s, SLOT_B / 2);
          tma3d_ef(sb + OFF_SLOT + s * SLOT_B + SLOT_B / 2, &maps.v16[blk], row0 + 960, 2, sb + BAR_FULL + 8 * s, pol);
          break;
        }
        mbar_expect_tx(sb + BAR_FULL + 8 * s, SLOT_B);
        tma3d_ef(sb + OFF_SLOT + s * SLOT_B, isv ? mv : mk, row0 + 64 * j, 0, sb + BAR_FULL + 8 * s, pol);
      }
#pragma unroll 1
      for (int u = 0; u < 14; u++) {
        uint32_t s, use;
        wo_slot(u, s, use);
        if (use > 0) mbar_wait(sb + BAR_EMPTY + 8 * s, (use - 1) & 1);
        mbar_expect_tx(sb + BAR_FULL + 8 * s, SLOT_B);
        tma3d(sb + OFF_SLOT + s * SLOT_B, mwo, kvh * 512 + 256 * (u & 1), u >> 1, sb + BAR_FULL + 8 * s);
      }
    }
  } else if (wg == 1) {
    asm volatile("setmaxnreg.dec.sync.aligned.u32 104;");
    nb_sync(0, 480);
    ROLE_IDS();
    float m[5], l[5];
#pragma unroll
    for (int r = 0; r < 5; r++) { m[r] = -INFINITY; l[r] = 0.f; }
    SCtx cx;
    {
      const uint32_t li = lane & 7, lm = lane >> 3;
      cx.pa01 = sb + OFF_P + (16 * wi + li + 8 * (lm & 1)) * 128 + (((lm >> 1) ^ li) << 4);
      cx.pa2 = sb + OFF_P + (128 + 8 * wi + li) * 128 + ((lm ^ li) << 4);
      const uint32_t r8 = lane >> 2;
      cx.sa01 = sb + OFF_SC + (40 * (r8 >> 1) + 2 * (2 * wi) + (r8 & 1)) * 4;
      cx.sa2 = sb + OFF_SC + (40 * (r8 >> 1) + 2 * (16 + wi) + (r8 & 1)) * 4;
      cx.wr = (lane & 3) == 0;
    }
    nb_sync(NB_Q, 384);
    if (tid == 128) PROF(3);
#pragma unroll 1
    for (int j = 0; j < 16; j++) s_tile(j, m, l, cx, wi, lane);
#pragma unroll
    for (int r = 0; r < 5; r++) {
      float lr = l[r];
      lr += __shfl_xor_sync(0xffffffffu, lr, 1);
      lr += __shfl_xor_sync(0xffffffffu, lr, 2);
      float inv;
      asm("rcp.approx.ftz.f32 %0, %1;" : "=f"(inv) : "f"(lr));
      if (cx.wr) sts32((r < 4 ? cx.sa01 + (r >> 1) * 64 + (r & 1) * 8 : cx.sa2) + (OFF_LINV - OFF_SC), inv);
    }
    nb_arrive(NB_O2, 384);
    uint32_t tid2, bid2;
    asm volatile("mov.u32 %0, %%tid.x;" : "=r"(tid2));
    asm volatile("mov.u32 %0, %%ctaid.x;" : "=r"(bid2));
    if (tid2 < 160) {
      if (tid2 == 128) {
        uint32_t target, z, it = 0;
        mbar_wait(sb + BAR_T, 0);
        asm volatile("ld.shared.u32 %0, [%1];" : "=r"(target) : "r"(sb + OFF_MISC) : "memory");
        do {
          asm volatile("ld.acquire.gpu.global.u32 %0, [%1];" : "=r"(z) : "l"(g_zero + ((bid2 >> 6) * 8 + (bid2 & 7)) * 32) : "memory");
          if (++it > (1u << 22)) __trap();
        } while ((int)(z - target) < 0);
        asm volatile("fence.proxy.async;" ::: "memory");
      }
#pragma unroll 1
      for (int p = 0; p < 7; p++) {
        nb_sync(NB_SF + (p & 1), 160);
        if (tid2 == 128) {
#pragma unroll
          for (int k = 4; k >= 0; k--) {
            asm volatile("cp.reduce.async.bulk.tensor.3d.global.shared::cta.add.tile.bulk_group [%0, {%1, %2, %3}], [%4];"
                         ::"l"(&maps.o), "r"(0), "r"((bid2 & 7) * 80 + 16 * k), "r"((bid2 >> 6) * 7 + p),
                         "r"(sb + OFF_ST + (k == 4 ? 16384 : (p & 1) * 8192 + k * 2048)) : "memory");
            if (k == 4 || k == 0) asm volatile("cp.async.bulk.commit_group;" ::: "memory");
          }
          asm volatile("cp.async.bulk.wait_group.read 1;" ::: "memory");
        }
        __syncwarp();
        if (p < 6) nb_arrive(nb_se((p + 1) & 1), 160);
        if (tid2 == 128) asm volatile("cp.async.bulk.wait_group.read 0;" ::: "memory");
        __syncwarp();
        if (p < 5) nb_arrive(NB_GO + (p & 1), 160);
      }
    }
    if (tid2 == 128) PROF(7);
  } else {
    asm volatile("setmaxnreg.inc.sync.aligned.u32 192;");
    ROLE_IDS();
    const int w = __shfl_sync(0xffffffffu, (tid >> 7) & 1, 0);
    const uint32_t li = lane & 7, lm = lane >> 3;
    {
      float acc[160];
#pragma unroll
      for (int i = 0; i < 160; i++) acc[i] = 0.f;
      reg_fence<160>(acc);
      nb_sync(0, 480);
      if (tid == 256) PROF(1);
      uint32_t st = 2, ph = 0, pst = 0, ok = 0;
#pragma unroll 1
      for (int t = 0; t < 28; t++) {
        if (!ok) mbar_wait(sb + BAR_WFULL + 8 * st, ph);
        const uint32_t nst = (st == 5) ? 0 : st + 1, nph = (nst == 2) ? ph ^ 1 : ph;
        ok = mbar_test(sb + BAR_WFULL + 8 * nst, nph);
        const uint32_t da = dlo(sb + OFF_W) + st * (WST_B >> 4) + w * (8192 >> 4);
        const uint32_t db = dlo(sb + OFF_Q) + (((t >> 2) * 10240 + (t & 3) * 32) >> 4);
        wg_fence();
        static_for<0, 4>([&](auto C) { constexpr int cc = decltype(C)::value; wgmma_n80_mk1<cc * 2048, 0>(acc + 40 * cc, da, db); });
        wg_commit();
        wg_wait<1>();
        if (t > 0 && lane == 0) mbar_arrive(sb + BAR_WEMPT + 8 * pst);
        pst = st;
        st = nst;
        ph = nph;
      }
      wg_wait<0>();
      reg_fence<160>(acc);
      if (tid == 256) PROF(2);
      const uint32_t qa = sb + OFF_Q + (80 * w + 8 * (lm >> 1) + li) * 128 + (((2 * wi + (lm & 1)) ^ li) << 4);
#pragma unroll
      for (int cc = 0; cc < 4; cc++) {
        if (cc == 2) nb_sync(NB_O, 256);
#pragma unroll
        for (int jj = 0; jj < 5; jj++) {
          const float* q = acc + 40 * cc + 8 * jj;
          stsm4t(qa + cc * QCHUNK + jj * 2048, pack_bf16(q[0], q[1]), pack_bf16(q[2], q[3]), pack_bf16(q[4], q[5]),
                 pack_bf16(q[6], q[7]));
        }
      }
      fence_async();
      nb_arrive(NB_Q, 384);
    }
    {
    float acc[160];
#pragma unroll
    for (int i = 0; i < 160; i++) acc[i] = 0.f;
    reg_fence<160>(acc);
#pragma unroll 1
    for (int j = 0; j < 16; j++) {
      const uint32_t pb = j & 1;
      nb_sync(NB_PFULL + pb, 384);
      if (j > 0) {
        const float4 f = lds128(sb + OFF_FLAG + pb * 16);
        if ((__float_as_uint(f.x) | __float_as_uint(f.y) | __float_as_uint(f.z) | __float_as_uint(f.w)) != 0) {
          const uint32_t sc = sb + OFF_SC + pb * 640 + (lane & 3) * 160;
#pragma unroll
          for (int g = 0; g < 10; g++) {
            const float4 a = lds128(sc + g * 16);
#pragma unroll
            for (int mb = 0; mb < 2; mb++) {
              float* q = acc + 80 * mb + 8 * g;
              q[0] *= a.x; q[1] *= a.y; q[2] *= a.x; q[3] *= a.y;
              q[4] *= a.z; q[5] *= a.w; q[6] *= a.z; q[7] *= a.w;
            }
          }
        }
      }
      uint32_t slot, use;
      kv_slot(j == 15 ? 31 : 2 * j + 2, slot, use);
      reg_fence<160>(acc);
      if (j < 15) nb_sync(NB_GO + w, 256);
      else if (w == 1) nb_sync(NB_O, 256);
      if (j == 15 && w == 0) mbar_wait(sb + BAR_VL, 0);
      else mbar_wait(sb + BAR_FULL + 8 * slot, use & 1);
      if (tid == 256) PROF(24 + j);
      const uint32_t da = dlo(sb + OFF_SLOT) + slot * (SLOT_B >> 4) + w * (16384 >> 4);
      const uint32_t db = dlo(sb + OFF_P) + pb * (QCHUNK >> 4);
      wg_fence();
      static_for<0, 4>([&](auto K) {
        constexpr int ks = decltype(K)::value;
        wgmma_n160_mk1<ks * 2048, ks * 32>(acc, da, db);
        wgmma_n160_mk1<8192 + ks * 2048, ks * 32>(acc + 80, da, db);
      });
      wg_commit();
      if (j == 15 && w == 0) nb_arrive(NB_O, 256);
      wg_wait<0>();
      reg_fence<160>(acc);
      if (lane == 0) mbar_arrive(sb + BAR_EMPTY + 8 * slot);
      if (j < 14) nb_arrive(NB_PEMPTY + pb, 384);
    }
    if (tid == 256) PROF(4);
    {
      const uint32_t oa = sb + OFF_Q + 2 * w * QCHUNK + (8 * (lm >> 1) + li) * 128 + (((2 * wi + (lm & 1)) ^ li) << 4);
#pragma unroll
      for (int mb = 0; mb < 2; mb++)
#pragma unroll
        for (int jj = 0; jj < 10; jj++) {
          const float* q = acc + 80 * mb + 8 * jj;
          stsm4t(oa + mb * QCHUNK + jj * 2048, pack_bf16(q[0], q[1]), pack_bf16(q[2], q[3]), pack_bf16(q[4], q[5]),
                 pack_bf16(q[6], q[7]));
        }
      fence_async();
    }
    }
    nb_sync(NB_O2, 384);
    if (tid == 256) PROF(5);
    constexpr uint32_t dob = dlo(sb + OFF_Q);
    const uint32_t sta = sb + OFF_ST + (8 * (lm >> 1) + li) * 128 + (((2 * wi + (lm & 1)) ^ li) << 4);
    float linv[40];
#pragma unroll
    for (int g = 0; g < 10; g++) {
      const float4 f = lds128(sb + OFF_LINV + (lane & 3) * 160 + g * 16);
      linv[4 * g] = f.x; linv[4 * g + 1] = f.y; linv[4 * g + 2] = f.z; linv[4 * g + 3] = f.w;
    }
#pragma unroll 1
    for (int p = w; p < 7; p += 2) {
      float acc[40], acc1[40];
      uint32_t slot0, use0, slot1, use1;
      wo_slot(2 * p, slot0, use0);
      wo_slot(2 * p + 1, slot1, use1);
      mbar_wait(sb + BAR_FULL + 8 * slot0, use0 & 1);
      if (p > 0) nb_sync(NB_ORD + w, 256);
      if (lane == 0 && wi == 0) PT(40 + p);
      uint32_t da = dlo(sb + OFF_SLOT) + slot0 * (SLOT_B >> 4);
      wg_fence();
      wgmma_n80_mk_z<0, 0>(acc, da, dob);
      static_for<1, 9>([&](auto K) {
        constexpr int ks = decltype(K)::value;
        wgmma_n80_mk1<ks * 2048, (ks >> 2) * QCHUNK + (ks & 3) * 32>(acc, da, dob);
      });
      const uint32_t ok1 = mbar_test(sb + BAR_FULL + 8 * slot1, use1 & 1);
      static_for<9, 16>([&](auto K) {
        constexpr int ks = decltype(K)::value;
        wgmma_n80_mk1<ks * 2048, (ks >> 2) * QCHUNK + (ks & 3) * 32>(acc, da, dob);
      });
      wg_commit();
      if (!ok1) mbar_wait(sb + BAR_FULL + 8 * slot1, use1 & 1);
      da = dlo(sb + OFF_SLOT) + slot1 * (SLOT_B >> 4);
      wg_fence();
      wgmma_n80_mk_z<0, 10240>(acc1, da, dob);
      static_for<1, 6>([&](auto K) {
        constexpr int ks = decltype(K)::value;
        wgmma_n80_mk1<ks * 2048, 10240 + (ks >> 2) * QCHUNK + (ks & 3) * 32>(acc1, da, dob);
      });
      wg_commit();
      wg_wait<1>();
      if (lane == 0) mbar_arrive_n(sb + BAR_EMPTY + 8 * slot0, 2);
      wg_fence();
      static_for<6, 16>([&](auto K) {
        constexpr int ks = decltype(K)::value;
        wgmma_n80_mk1<ks * 2048, 10240 + (ks >> 2) * QCHUNK + (ks & 3) * 32>(acc1, da, dob);
      });
      wg_commit();
      if (p < 6) nb_arrive(NB_ORD + (w ^ 1), 256);
      wg_wait<0>();
      reg_fence<40>(acc);
      reg_fence<40>(acc1);
      if (lane == 0) mbar_arrive_n(sb + BAR_EMPTY + 8 * slot1, 2);
#pragma unroll
      for (int i = 0; i < 40; i++)
        acc[i] = fmaf(acc[i], linv[2 * (i >> 2) + (i & 1)], acc1[i] * linv[20 + 2 * (i >> 2) + (i & 1)]);
      uint32_t pk[20];
#pragma unroll
      for (int i = 0; i < 20; i++) pk[i] = pack_bf16(acc[2 * i], acc[2 * i + 1]);
      if (p > 1) nb_sync(NB_GO + w, 160);
#pragma unroll
      for (int k = 0; k < 4; k++) stsm4t(sta + w * 8192 + k * 2048, pk[4 * k], pk[4 * k + 1], pk[4 * k + 2], pk[4 * k + 3]);
      if (p > 0) nb_sync(nb_se(w), 160);
      stsm4t(sta + 16384, pk[16], pk[17], pk[18], pk[19]);
      fence_async();
      nb_arrive(NB_SF + w, 160);
      if (lane == 0 && wi == 0) PT(47 + p);
    }
    if (tid == 256) PROF(6);
    if (lane == 0 && wi == 0) PT(60 - w);
  }
}

typedef CUresult (*EncodeFn)(CUtensorMap*, CUtensorMapDataType, cuuint32_t, void*, const cuuint64_t*, const cuuint64_t*,
                             const cuuint32_t*, const cuuint32_t*, CUtensorMapInterleave, CUtensorMapSwizzle,
                             CUtensorMapL2promotion, CUtensorMapFloatOOBfill);

void encode3d(EncodeFn enc, CUtensorMap* m, void* p, uint64_t rows, uint64_t cols, uint32_t box_rows,
              uint32_t box_blocks) {
  cuuint64_t dims[3] = {64, rows, cols / 64};
  cuuint64_t strides[2] = {cols * 2, 128};
  cuuint32_t box[3] = {64, box_rows, box_blocks};
  cuuint32_t es[3] = {1, 1, 1};
  enc(m, CU_TENSOR_MAP_DATA_TYPE_BFLOAT16, 3, p, dims, strides, box, es, CU_TENSOR_MAP_INTERLEAVE_NONE,
      CU_TENSOR_MAP_SWIZZLE_128B,
      cols == 256 ? CU_TENSOR_MAP_L2_PROMOTION_L2_256B : CU_TENSOR_MAP_L2_PROMOTION_L2_128B,
      CU_TENSOR_MAP_FLOAT_OOB_FILL_NONE);
}

}

extern "C" void kernel_launch(void* const* d_in, const int* in_sizes, int n_in, void* d_out, int out_size) {
  static EncodeFn enc = nullptr;
  if (!enc) {
    void* fn = nullptr;
    cudaDriverEntryPointQueryResult qr;
    cudaGetDriverEntryPoint("cuTensorMapEncodeTiled", &fn, cudaEnableDefault, &qr);
    enc = (EncodeFn)fn;
    cudaFuncSetAttribute(fused_gqa_kernel, cudaFuncAttributeMaxDynamicSharedMemorySize, SMEM_BYTES);
  }
  Maps maps;
  for (int blk = 0; blk < 2; blk++) {
    encode3d(enc, &maps.m[blk * 5 + 0], d_in[blk * 5 + 0], 640, 448, 80, 1);
    encode3d(enc, &maps.m[blk * 5 + 1], d_in[blk * 5 + 1], 65536, 256, 64, 4);
    encode3d(enc, &maps.m[blk * 5 + 2], d_in[blk * 5 + 2], 65536, 256, 64, 4);
    encode3d(enc, &maps.m[blk * 5 + 3], d_in[blk * 5 + 3], 448, 4096, 16, 8);
    encode3d(enc, &maps.m[blk * 5 + 4], d_in[blk * 5 + 4], 4096, 448, 256, 1);
    encode3d(enc, &maps.k8[blk], d_in[blk * 5 + 1], 65536, 256, 64, 1);
    encode3d(enc, &maps.v16[blk], d_in[blk * 5 + 2], 65536, 256, 64, 2);
  }
  encode3d(enc, &maps.o, d_out, 640, 896, 16, 1);
  fused_gqa_kernel<<<NCTA, NTHREADS, SMEM_BYTES>>>(maps, (__nv_bfloat16*)d_out);
}
```

```cpp
#include <cuda_runtime.h>
#include <cuda_bf16.h>
#include <cuda.h>
#include <stdint.h>

namespace {

constexpr int NCTA = 128;
constexpr int NTHREADS = 512;

constexpr uint32_t SB = 0x400;
constexpr uint32_t OFF_Q     = 0;
constexpr uint32_t QCHUNK    = 20480;
constexpr uint32_t OFF_SLOT  = 81920;
constexpr uint32_t SLOT_B    = 32768;
constexpr uint32_t OFF_P     = OFF_SLOT + 3 * SLOT_B;
constexpr uint32_t OFF_W     = OFF_SLOT + SLOT_B;
constexpr uint32_t WST_B     = 16384;
constexpr uint32_t OFF_SC    = OFF_P + 2 * QCHUNK;
constexpr uint32_t OFF_FLAG  = OFF_SC + 1280;
constexpr uint32_t OFF_LINV  = OFF_FLAG + 32;
constexpr uint32_t OFF_ST    = OFF_P + SLOT_B;
constexpr uint32_t OFF_BAR   = OFF_ST + 18432;
constexpr uint32_t BAR_FULL  = OFF_BAR;
constexpr uint32_t BAR_EMPTY = BAR_FULL + 32;
constexpr uint32_t BAR_WFULL = BAR_EMPTY + 32;
constexpr uint32_t BAR_WEMPT = BAR_WFULL + 48;
constexpr uint32_t BAR_T     = BAR_WEMPT + 48;
constexpr uint32_t BAR_VL    = BAR_T + 8;
constexpr uint32_t OFF_MISC  = BAR_VL + 8;
constexpr uint32_t SMEM_BYTES = OFF_MISC + 16;

#define PACE_TAU 1350
#define PACE_T0 3000
#define PACE_MIN 1250

struct Maps {
  CUtensorMap m[10];
  CUtensorMap k8[2];
  CUtensorMap v16[2];
  CUtensorMap o;
};

__device__ unsigned int g_zero[16 * 32];

__device__ __forceinline__ void mbar_init(uint32_t bar, uint32_t cnt) {
  asm volatile("mbarrier.init.shared::cta.b64 [%0], %1;" ::"r"(bar), "r"(cnt) : "memory");
}
__device__ __forceinline__ void mbar_expect_tx(uint32_t bar, uint32_t bytes) {
  asm volatile("mbarrier.arrive.expect_tx.shared::cta.b64 _, [%0], %1;" ::"r"(bar), "r"(bytes) : "memory");
}
__device__ __forceinline__ void mbar_arrive(uint32_t bar) {
  asm volatile("mbarrier.arrive.shared::cta.b64 _, [%0];" ::"r"(bar) : "memory");
}
__device__ __forceinline__ void mbar_arrive_n(uint32_t bar, uint32_t n) {
  asm volatile("mbarrier.arrive.shared::cta.b64 _, [%0], %1;" ::"r"(bar), "r"(n) : "memory");
}
__device__ __forceinline__ void mbar_wait(uint32_t bar, uint32_t parity) {
  asm volatile(
      "{\n.reg .pred p;\n.reg .u32 c;\nmov.u32 c, 0;\n"
      "W_LOOP:\n"
      "mbarrier.try_wait.parity.shared::cta.b64 p, [%0], %1;\n"
      "@p bra W_DONE;\n"
      "add.u32 c, c, 1;\n"
      "setp.lt.u32 p, c, 0x400000;\n"
      "@p bra W_LOOP;\n"
      "trap;\n"
      "W_DONE:\n}\n" ::"r"(bar), "r"(parity) : "memory");
}
__device__ __forceinline__ uint32_t mbar_test(uint32_t bar, uint32_t parity) {
  uint32_t ok;
  asm volatile("{\n.reg .pred p;\nmbarrier.test_wait.parity.shared::cta.b64 p, [%1], %2;\nselp.u32 %0, 1, 0, p;\n}\n"
               : "=r"(ok) : "r"(bar), "r"(parity) : "memory");
  return ok;
}
__device__ __forceinline__ void nb_sync(uint32_t id, uint32_t n) { asm volatile("bar.sync %0, %1;" ::"r"(id), "r"(n) : "memory"); }
__device__ __forceinline__ void nb_arrive(uint32_t id, uint32_t n) { asm volatile("bar.arrive %0, %1;" ::"r"(id), "r"(n) : "memory"); }
constexpr uint32_t NB_O = 1, NB_PFULL = 2, NB_PEMPTY = 4, NB_GO = 6, NB_Q = 8, NB_ORD = 10, NB_O2 = 12, NB_S = 13, NB_SF = 14;
__device__ __forceinline__ uint32_t nb_se(uint32_t w) { return w ? NB_S : NB_Q; }
__device__ __forceinline__ void tma3d(uint32_t dst, const CUtensorMap* m, int c1, int c2, uint32_t bar) {
  asm volatile(
      "cp.async.bulk.tensor.3d.shared::cluster.global.mbarrier::complete_tx::bytes [%0], [%1, {%2, %3, %4}], [%5];"
      ::"r"(dst), "l"(m), "r"(0), "r"(c1), "r"(c2), "r"(bar) : "memory");
}
__device__ __forceinline__ void tma3d_ef(uint32_t dst, const CUtensorMap* m, int c1, int c2, uint32_t bar, uint64_t pol) {
  asm volatile(
      "cp.async.bulk.tensor.3d.shared::cluster.global.mbarrier::complete_tx::bytes.L2::cache_hint [%0], [%1, {%2, %3, %4}], [%5], %6;"
      ::"r"(dst), "l"(m), "r"(0), "r"(c1), "r"(c2), "r"(bar), "l"(pol) : "memory");
}
__device__ __forceinline__ void tma3d_pf(const CUtensorMap* m, int c1, int c2) {
  asm volatile("cp.async.bulk.prefetch.tensor.3d.L2.global [%0, {%1, %2, %3}];" ::"l"(m), "r"(0), "r"(c1), "r"(c2)
               : "memory");
}
__device__ __forceinline__ void wg_fence() { asm volatile("wgmma.fence.sync.aligned;" ::: "memory"); }
__device__ __forceinline__ void wg_commit() { asm volatile("wgmma.commit_group.sync.aligned;" ::: "memory"); }
template <int N>
__device__ __forceinline__ void wg_wait() { asm volatile("wgmma.wait_group.sync.aligned %0;" ::"n"(N) : "memory"); }
__device__ __forceinline__ void fence_async() { asm volatile("fence.proxy.async.shared::cta;" ::: "memory"); }
template <int N>
__device__ __forceinline__ void reg_fence(float* d) {
#pragma unroll
  for (int i = 0; i < N; i++) asm volatile("" : "+f"(d[i])::"memory");
}
__device__ __forceinline__ constexpr uint32_t dlo(uint32_t saddr) { return ((saddr & 0x3FFFFu) >> 4) | (1u << 16); }
template <int V>
struct IC { static constexpr int value = V; };
template <int I, int N, class F>
__device__ __forceinline__ void static_for(F&& f) {
  if constexpr (I < N) {
    f(IC<I>{});
    static_for<I + 1, N>(f);
  }
}
__device__ __forceinline__ uint32_t pack_bf16(float lo, float hi) {
  uint32_t r;
  asm("cvt.rn.bf16x2.f32 %0, %1, %2;" : "=r"(r) : "f"(hi), "f"(lo));
  return r;
}
template <uint32_t XR, uint32_t OFF>
__device__ __forceinline__ void stsm4_o(uint32_t a, uint32_t r0, uint32_t r1, uint32_t r2, uint32_t r3) {
  asm volatile("{\n.reg .b32 t;\nxor.b32 t, %0, %6;\nstmatrix.sync.aligned.m8n8.x4.shared.b16 [t + %5], {%1, %2, %3, %4};\n}\n"
               ::"r"(a), "r"(r0), "r"(r1), "r"(r2), "r"(r3), "n"(OFF), "n"(XR) : "memory");
}
__device__ __forceinline__ void stsm4t(uint32_t a, uint32_t r0, uint32_t r1, uint32_t r2, uint32_t r3) {
  asm volatile("stmatrix.sync.aligned.m8n8.x4.trans.shared.b16 [%0], {%1, %2, %3, %4};" ::"r"(a), "r"(r0), "r"(r1),
               "r"(r2), "r"(r3) : "memory");
}
__device__ __forceinline__ float ex2(float x) {
  float y;
  asm("ex2.approx.ftz.f32 %0, %1;" : "=f"(y) : "f"(x));
  return y;
}
__device__ __forceinline__ float4 lds128(uint32_t a) {
  float4 v;
  asm volatile("ld.shared.v4.f32 {%0, %1, %2, %3}, [%4];" : "=f"(v.x), "=f"(v.y), "=f"(v.z), "=f"(v.w) : "r"(a) : "memory");
  return v;
}
__device__ __forceinline__ void sts32(uint32_t a, float v) {
  asm volatile("st.shared.f32 [%0], %1;" ::"r"(a), "f"(v) : "memory");
}
template <uint32_t OA, uint32_t OB, uint32_t HIA = 0x40000040u>
__device__ __forceinline__ void wgmma_n64_kk_z(float* d, uint32_t a, uint32_t b) {
  asm volatile(
      "{\n.reg .b32 ta, tb;\n.reg .b64 da, db;\nadd.u32 ta, %32, %34;\nadd.u32 tb, %33, %35;\nmov.b64 da, {ta, %36};\nmov.b64 db, {tb, 0x40000040};\n"
      "wgmma.mma_async.sync.aligned.m64n64k16.f32.bf16.bf16 {"
      "%0, %1, %2, %3, %4, %5, %6, %7, %8, %9, %10, %11, %12, %13, %14, %15,"
      "%16, %17, %18, %19, %20, %21, %22, %23, %24, %25, %26, %27, %28, %29, %30, %31}, da, db, 0, 1, 1, 0, 0;\n}\n"
      : "=f"(d[0]), "=f"(d[1]), "=f"(d[2]), "=f"(d[3]), "=f"(d[4]), "=f"(d[5]), "=f"(d[6]), "=f"(d[7]),
        "=f"(d[8]), "=f"(d[9]), "=f"(d[10]), "=f"(d[11]), "=f"(d[12]), "=f"(d[13]), "=f"(d[14]), "=f"(d[15]),
        "=f"(d[16]), "=f"(d[17]), "=f"(d[18]), "=f"(d[19]), "=f"(d[20]), "=f"(d[21]), "=f"(d[22]), "=f"(d[23]),
        "=f"(d[24]), "=f"(d[25]), "=f"(d[26]), "=f"(d[27]), "=f"(d[28]), "=f"(d[29]), "=f"(d[30]), "=f"(d[31])
      : "r"(a), "r"(b), "n"(OA >> 4), "n"(OB >> 4), "n"(HIA));
}

template <uint32_t OA, uint32_t OB, uint32_t HIA = 0x40000040u>
__device__ __forceinline__ void wgmma_n64_kk(float* d, uint32_t a, uint32_t b) {
  asm volatile(
      "{\n.reg .b32 ta, tb;\n.reg .b64 da, db;\nadd.u32 ta, %32, %34;\nadd.u32 tb, %33, %35;\nmov.b64 da, {ta, %36};\nmov.b64 db, {tb, 0x40000040};\n"
      "wgmma.mma_async.sync.aligned.m64n64k16.f32.bf16.bf16 {"
      "%0, %1, %2, %3, %4, %5, %6, %7, %8, %9, %10, %11, %12, %13, %14, %15,"
      "%16, %17, %18, %19, %20, %21, %22, %23, %24, %25, %26, %27, %28, %29, %30, %31}, da, db, 1, 1, 1, 0, 0;\n}\n"
      : "+f"(d[0]), "+f"(d[1]), "+f"(d[2]), "+f"(d[3]), "+f"(d[4]), "+f"(d[5]), "+f"(d[6]), "+f"(d[7]),
        "+f"(d[8]), "+f"(d[9]), "+f"(d[10]), "+f"(d[11]), "+f"(d[12]), "+f"(d[13]), "+f"(d[14]), "+f"(d[15]),
        "+f"(d[16]), "+f"(d[17]), "+f"(d[18]), "+f"(d[19]), "+f"(d[20]), "+f"(d[21]), "+f"(d[22]), "+f"(d[23]),
        "+f"(d[24]), "+f"(d[25]), "+f"(d[26]), "+f"(d[27]), "+f"(d[28]), "+f"(d[29]), "+f"(d[30]), "+f"(d[31])
      : "r"(a), "r"(b), "n"(OA >> 4), "n"(OB >> 4), "n"(HIA));
}

template <uint32_t OA, uint32_t OB, uint32_t HIA = 0x40000040u>
__device__ __forceinline__ void wgmma_n80_mk_z(float* d, uint32_t a, uint32_t b) {
  asm volatile(
      "{\n.reg .b32 ta, tb;\n.reg .b64 da, db;\nadd.u32 ta, %40, %42;\nadd.u32 tb, %41, %43;\nmov.b64 da, {ta, %44};\nmov.b64 db, {tb, 0x40000040};\n"
      "wgmma.mma_async.sync.aligned.m64n80k16.f32.bf16.bf16 {"
      "%0, %1, %2, %3, %4, %5, %6, %7, %8, %9, %10, %11, %12, %13, %14, %15,"
      "%16, %17, %18, %19, %20, %21, %22, %23, %24, %25, %26, %27, %28, %29, %30, %31,"
      "%32, %33, %34, %35, %36, %37, %38, %39}, da, db, 0, 1, 1, 1, 0;\n}\n"
      : "=f"(d[0]), "=f"(d[1]), "=f"(d[2]), "=f"(d[3]), "=f"(d[4]), "=f"(d[5]), "=f"(d[6]), "=f"(d[7]),
        "=f"(d[8]), "=f"(d[9]), "=f"(d[10]), "=f"(d[11]), "=f"(d[12]), "=f"(d[13]), "=f"(d[14]), "=f"(d[15]),
        "=f"(d[16]), "=f"(d[17]), "=f"(d[18]), "=f"(d[19]), "=f"(d[20]), "=f"(d[21]), "=f"(d[22]), "=f"(d[23]),
        "=f"(d[24]), "=f"(d[25]), "=f"(d[26]), "=f"(d[27]), "=f"(d[28]), "=f"(d[29]), "=f"(d[30]), "=f"(d[31]),
        "=f"(d[32]), "=f"(d[33]), "=f"(d[34]), "=f"(d[35]), "=f"(d[36]), "=f"(d[37]), "=f"(d[38]), "=f"(d[39])
      : "r"(a), "r"(b), "n"(OA >> 4), "n"(OB >> 4), "n"(HIA));
}

template <uint32_t OA, uint32_t OB, uint32_t HIA = 0x40000040u>
__device__ __forceinline__ void wgmma_n80_mk1(float* d, uint32_t a, uint32_t b) {
  asm volatile(
      "{\n.reg .b32 ta, tb;\n.reg .b64 da, db;\nadd.u32 ta, %40, %42;\nadd.u32 tb, %41, %43;\nmov.b64 da, {ta, %44};\nmov.b64 db, {tb, 0x40000040};\n"
      "wgmma.mma_async.sync.aligned.m64n80k16.f32.bf16.bf16 {"
      "%0, %1, %2, %3, %4, %5, %6, %7, %8, %9, %10, %11, %12, %13, %14, %15,"
      "%16, %17, %18, %19, %20, %21, %22, %23, %24, %25, %26, %27, %28, %29, %30, %31,"
      "%32, %33, %34, %35, %36, %37, %38, %39}, da, db, 1, 1, 1, 1, 0;\n}\n"
      : "+f"(d[0]), "+f"(d[1]), "+f"(d[2]), "+f"(d[3]), "+f"(d[4]), "+f"(d[5]), "+f"(d[6]), "+f"(d[7]),
        "+f"(d[8]), "+f"(d[9]), "+f"(d[10]), "+f"(d[11]), "+f"(d[12]), "+f"(d[13]), "+f"(d[14]), "+f"(d[15]),
        "+f"(d[16]), "+f"(d[17]), "+f"(d[18]), "+f"(d[19]), "+f"(d[20]), "+f"(d[21]), "+f"(d[22]), "+f"(d[23]),
        "+f"(d[24]), "+f"(d[25]), "+f"(d[26]), "+f"(d[27]), "+f"(d[28]), "+f"(d[29]), "+f"(d[30]), "+f"(d[31]),
        "+f"(d[32]), "+f"(d[33]), "+f"(d[34]), "+f"(d[35]), "+f"(d[36]), "+f"(d[37]), "+f"(d[38]), "+f"(d[39])
      : "r"(a), "r"(b), "n"(OA >> 4), "n"(OB >> 4), "n"(HIA));
}

template <uint32_t OA, uint32_t OB, uint32_t HIA = 0x40000040u>
__device__ __forceinline__ void wgmma_n160_mk1(float* d, uint32_t a, uint32_t b) {
  asm volatile(
      "{\n.reg .b32 ta, tb;\n.reg .b64 da, db;\nadd.u32 ta, %80, %82;\nadd.u32 tb, %81, %83;\nmov.b64 da, {ta, %84};\nmov.b64 db, {tb, 0x40000040};\n"
      "wgmma.mma_async.sync.aligned.m64n160k16.f32.bf16.bf16 {"
      "%0, %1, %2, %3, %4, %5, %6, %7, %8, %9, %10, %11, %12, %13, %14, %15,"
      "%16, %17, %18, %19, %20, %21, %22, %23, %24, %25, %26, %27, %28, %29, %30, %31,"
      "%32, %33, %34, %35, %36, %37, %38, %39, %40, %41, %42, %43, %44, %45, %46, %47,"
      "%48, %49, %50, %51, %52, %53, %54, %55, %56, %57, %58, %59, %60, %61, %62, %63,"
      "%64, %65, %66, %67, %68, %69, %70, %71, %72, %73, %74, %75, %76, %77, %78, %79}, da, db, 1, 1, 1, 1, 0;\n}\n"
      : "+f"(d[0]), "+f"(d[1]), "+f"(d[2]), "+f"(d[3]), "+f"(d[4]), "+f"(d[5]), "+f"(d[6]), "+f"(d[7]),
        "+f"(d[8]), "+f"(d[9]), "+f"(d[10]), "+f"(d[11]), "+f"(d[12]), "+f"(d[13]), "+f"(d[14]), "+f"(d[15]),
        "+f"(d[16]), "+f"(d[17]), "+f"(d[18]), "+f"(d[19]), "+f"(d[20]), "+f"(d[21]), "+f"(d[22]), "+f"(d[23]),
        "+f"(d[24]), "+f"(d[25]), "+f"(d[26]), "+f"(d[27]), "+f"(d[28]), "+f"(d[29]), "+f"(d[30]), "+f"(d[31]),
        "+f"(d[32]), "+f"(d[33]), "+f"(d[34]), "+f"(d[35]), "+f"(d[36]), "+f"(d[37]), "+f"(d[38]), "+f"(d[39]),
        "+f"(d[40]), "+f"(d[41]), "+f"(d[42]), "+f"(d[43]), "+f"(d[44]), "+f"(d[45]), "+f"(d[46]), "+f"(d[47]),
        "+f"(d[48]), "+f"(d[49]), "+f"(d[50]), "+f"(d[51]), "+f"(d[52]), "+f"(d[53]), "+f"(d[54]), "+f"(d[55]),
        "+f"(d[56]), "+f"(d[57]), "+f"(d[58]), "+f"(d[59]), "+f"(d[60]), "+f"(d[61]), "+f"(d[62]), "+f"(d[63]),
        "+f"(d[64]), "+f"(d[65]), "+f"(d[66]), "+f"(d[67]), "+f"(d[68]), "+f"(d[69]), "+f"(d[70]), "+f"(d[71]),
        "+f"(d[72]), "+f"(d[73]), "+f"(d[74]), "+f"(d[75]), "+f"(d[76]), "+f"(d[77]), "+f"(d[78]), "+f"(d[79])
      : "r"(a), "r"(b), "n"(OA >> 4), "n"(OB >> 4), "n"(HIA));
}

__device__ __forceinline__ void kv_slot(int i, uint32_t& slot, uint32_t& use) {
  use = (uint32_t)i / 3u;
  slot = (uint32_t)i - use * 3u;
}
__device__ __forceinline__ void wo_slot(int u, uint32_t& slot, uint32_t& use) {
  uint32_t r = u & 3, q = u >> 2;
  slot = (r == 0) ? 2u : (r == 3) ? 3u : (r - 1u);
  use = q + ((r == 0) ? 10u : (r == 3) ? 0u : 11u);
}

struct SCtx {
  uint32_t pa01, pa2, sa01, sa2;
  bool wr;
};

template <int BLK>
__device__ __forceinline__ void qk_issue(float* s, uint32_t dk) {
  constexpr uint32_t dq = dlo(SB + OFF_Q + BLK * 8192);
  constexpr uint32_t HI = (BLK == 2) ? 0x40000020u : 0x40000040u;
  wg_fence();
  constexpr uint32_t T = BLK << 20;
  wgmma_n64_kk_z<0, T, HI>(s, dq, dk);
  static_for<1, 16>([&](auto I) {
    constexpr int ks = decltype(I)::value;
    wgmma_n64_kk<(ks >> 2) * QCHUNK + (ks & 3) * 32, T + (ks >> 2) * 8192 + (ks & 3) * 32, HI>(s, dq, dk);
  });
  wg_commit();
}

template <int BLK, class F>
__device__ __forceinline__ void softmax_blk(float* s, float* mc, float* l, uint32_t& flag, const SCtx& cx, F&& mid) {
  constexpr float c = 0.0625f * 1.4426950408889634f;
  constexpr int NR = (BLK == 2) ? 1 : 2;
  float mx[NR], alpha[NR];
  bool need = false;
#pragma unroll
  for (int r = 0; r < NR; r++) {
    float v0 = fmaxf(s[2 * r], s[2 * r + 1]), v1 = fmaxf(s[2 * r + 4], s[2 * r + 5]);
#pragma unroll
    for (int g = 2; g < 8; g += 2) {
      v0 = fmaxf(v0, fmaxf(s[2 * r + 4 * g], s[2 * r + 4 * g + 1]));
      v1 = fmaxf(v1, fmaxf(s[2 * r + 4 * g + 4], s[2 * r + 4 * g + 5]));
    }
    mx[r] = fmaxf(v0, v1) * c;
    need |= !(mx[r] - mc[2 * BLK + r] <= 8.f);
    alpha[r] = 1.f;
  }
  if (__any_sync(0xffffffffu, need)) {
#pragma unroll
    for (int r = 0; r < NR; r++) mx[r] = fmaxf(mx[r], __shfl_xor_sync(0xffffffffu, mx[r], 1));
#pragma unroll
    for (int r = 0; r < NR; r++) mx[r] = fmaxf(mx[r], __shfl_xor_sync(0xffffffffu, mx[r], 2));
#pragma unroll
    for (int r = 0; r < NR; r++) {
      const float mo = mc[2 * BLK + r];
      const float mn = fmaxf(mo, mx[r]);
      alpha[r] = ex2(mo - mn);
      mc[2 * BLK + r] = mn;
      l[2 * BLK + r] *= alpha[r];
    }
    flag = 1;
  }
#pragma unroll
  for (int r = 0; r < NR; r++) {
    const float nm = -mc[2 * BLK + r];
    float sum0 = l[2 * BLK + r], sum1 = 0.f;
#pragma unroll
    for (int g = 0; g < 8; g++) {
      const float p0 = ex2(fmaf(s[2 * r + 4 * g], c, nm));
      const float p1 = ex2(fmaf(s[2 * r + 4 * g + 1], c, nm));
      s[2 * r + 4 * g] = p0;
      s[2 * r + 4 * g + 1] = p1;
      sum0 += p0;
      sum1 += p1;
    }
    const float lr = sum0 + sum1;
    l[2 * BLK + r] = lr;
    alpha[r] = fmaf(lr, 0.f, alpha[r]);
    if (r == 0) mid();
  }
  if (BLK < 2) {
    static_for<0, 4>([&](auto G) {
      constexpr int g = decltype(G)::value;
      const float* q = s + g * 8;
      stsm4_o<(g << 5), BLK * 8192>(cx.pa01, pack_bf16(q[0], q[1]), pack_bf16(q[2], q[3]), pack_bf16(q[4], q[5]),
                                    pack_bf16(q[6], q[7]));
    });
    if (cx.wr) {
      sts32(cx.sa01 + BLK * 64, alpha[0]);
      sts32(cx.sa01 + BLK * 64 + 8, alpha[NR - 1]);
    }
  } else {
    static_for<0, 2>([&](auto G) {
      constexpr int g = decltype(G)::value;
      const float* q = s + g * 16;
      stsm4_o<(g << 6), 0>(cx.pa2, pack_bf16(q[0], q[1]), pack_bf16(q[4], q[5]), pack_bf16(q[8], q[9]),
                           pack_bf16(q[12], q[13]));
    });
    if (cx.wr) sts32(cx.sa2, alpha[0]);
  }
}

__device__ __forceinline__ void s_tile(int j, float* mc, float* l, SCtx& cx, int wi, int lane) {
  constexpr uint32_t sb = SB;
  float sX[32], sY[32];
  uint32_t flag = 0, slot, use;
  const uint32_t pb = j & 1;
  kv_slot(j == 0 ? 0 : 2 * j - 1, slot, use);
  mbar_wait(sb + BAR_FULL + 8 * slot, use & 1);
  const uint32_t dk = dlo(sb + OFF_SLOT) + slot * (SLOT_B >> 4);
  qk_issue<2>(sX, dk);
  qk_issue<0>(sY, dk);
  if (j >= 2) nb_sync(NB_PEMPTY + pb, 384);
  wg_wait<1>();
  reg_fence<32>(sX);
  softmax_blk<2>(sX, mc, l, flag, cx, [] {});
  qk_issue<1>(sX, dk);
  if (j >= 1) nb_arrive(NB_GO, 384);
  wg_wait<1>();
  reg_fence<32>(sY);
  softmax_blk<0>(sY, mc, l, flag, cx, [&] {
    wg_wait<0>();
    if (lane == 0) mbar_arrive_n(sb + BAR_EMPTY + 8 * slot, 2);
  });
  reg_fence<32>(sX);
  softmax_blk<1>(sX, mc, l, flag, cx, [] {});
  if (lane == 0) asm volatile("st.shared.u32 [%0], %1;" ::"r"(sb + OFF_FLAG + pb * 16 + wi * 4), "r"(flag) : "memory");
  fence_async();
  nb_arrive(NB_PFULL + pb, 384);
  const uint32_t dp = pb ? (0u - QCHUNK) : QCHUNK, ds = pb ? (0u - 640u) : 640u;
  cx.pa01 += dp; cx.pa2 += dp; cx.sa01 += ds; cx.sa2 += ds;
}

__global__ void __launch_bounds__(NTHREADS, 1)
fused_gqa_kernel(const __grid_constant__ Maps maps, __nv_bfloat16* __restrict__ out) {
  extern __shared__ uint8_t smem_raw[];
  constexpr uint32_t sb = SB;
  if ((uint32_t)__cvta_generic_to_shared(smem_raw) != sb) __trap();
  const int wg = __shfl_sync(0xffffffffu, threadIdx.x >> 7, 0);
#define ROLE_IDS()                                                   \
  int tid, bid;                                                      \
  asm volatile("mov.u32 %0, %%tid.x;" : "=r"(tid));                  \
  asm volatile("mov.u32 %0, %%ctaid.x;" : "=r"(bid));                \
  const int wi = __shfl_sync(0xffffffffu, (tid >> 5) & 3, 0);        \
  const int lane = tid & 31;                                         \
  const int blk = bid >> 6, kvh = (bid >> 3) & 7, b = bid & 7;       \
  (void)wi; (void)lane; (void)blk; (void)kvh; (void)b

  if (threadIdx.x == 0) {
    for (int s = 0; s < 4; s++) {
      mbar_init(sb + BAR_FULL + 8 * s, 1);
      mbar_init(sb + BAR_EMPTY + 8 * s, 8);
    }
    for (int s = 0; s < 6; s++) {
      mbar_init(sb + BAR_WFULL + 8 * s, 1);
      mbar_init(sb + BAR_WEMPT + 8 * s, 8);
    }
    mbar_init(sb + BAR_T, 1);
    mbar_init(sb + BAR_VL, 1);
    asm volatile("fence.mbarrier_init.release.cluster;" ::: "memory");
    fence_async();
  }
  if (threadIdx.x < 32) {
    nb_arrive(0, 480);
    nb_arrive(15, 64);
    if (threadIdx.x == 0) {
      const int blk = blockIdx.x >> 6, kvh = (blockIdx.x >> 3) & 7, b = blockIdx.x & 7;
      const CUtensorMap* mx0 = &maps.m[blk * 5 + 0];
      const CUtensorMap* mw0 = &maps.m[blk * 5 + 3];
      static_for<0, 2>([&](auto T) {
        constexpr int t = decltype(T)::value, st = (t + 2) % 6, xc = t ? t - 1 : 0;
        constexpr bool hx = (t == 0) || (xc >= 1);
        mbar_expect_tx(sb + BAR_WFULL + 8 * st, hx ? WST_B + 10240 : WST_B);
        if constexpr (t == 0) tma3d(sb + OFF_Q, mx0, b * 80, 0, sb + BAR_WFULL + 8 * st);
        tma3d(sb + OFF_W + st * WST_B, mw0, 16 * t, kvh * 8, sb + BAR_WFULL + 8 * st);
        if constexpr (t > 0 && hx) tma3d(sb + OFF_Q + xc * 10240, mx0, b * 80, xc, sb + BAR_WFULL + 8 * st);
      });
    }
    __syncwarp();
  }

  if (wg == 0) {
    asm volatile("setmaxnreg.dec.sync.aligned.u32 24;");
    ROLE_IDS();
    if (wi == 1) nb_sync(15, 64);
    if (wi > 1) nb_sync(0, 480);
    if (tid == 32) {
      const CUtensorMap* mx0 = &maps.m[blk * 5 + 0];
      const CUtensorMap* mw0 = &maps.m[blk * 5 + 3];
      static_for<2, 6>([&](auto T) {
        constexpr int t = decltype(T)::value, st = (t + 2) % 6, xc = t - 1;
        constexpr bool hx = (xc >= 1);
        mbar_expect_tx(sb + BAR_WFULL + 8 * st, hx ? WST_B + 10240 : WST_B);
        tma3d(sb + OFF_W + st * WST_B, mw0, 16 * t, kvh * 8, sb + BAR_WFULL + 8 * st);
        if constexpr (hx) tma3d(sb + OFF_Q + xc * 10240, mx0, b * 80, xc, sb + BAR_WFULL + 8 * st);
      });
    }
    if (tid >= 64 && tid < 70) {
      const CUtensorMap* m = (tid == 64) ? &maps.k8[blk] : (tid == 68) ? &maps.v16[blk] : (tid == 69) ? &maps.o
                                                         : &maps.m[blk * 5 + (tid == 65 ? 1 : tid == 66 ? 2 : 4)];
      asm volatile("prefetch.tensormap [%0];" ::"l"(m) : "memory");
    }
    if (wi == 3) {
      __nanosleep(20000);
      __nv_bfloat16* o = out + (size_t)(b * 80 + kvh * 10) * 896 + blk * 448;
#pragma unroll 1
      for (int r = 0; r < 10; r++) {
        *reinterpret_cast<uint4*>(o + r * 896 + lane * 8) = make_uint4(0, 0, 0, 0);
        if (lane < 24) *reinterpret_cast<uint4*>(o + r * 896 + 256 + lane * 8) = make_uint4(0, 0, 0, 0);
      }
      __threadfence();
      __syncwarp();
      if (lane == 0) {
        uint32_t old;
        asm volatile("atom.release.gpu.global.add.u32 %0, [%1], 1;" : "=r"(old) : "l"(g_zero + (blk * 8 + b) * 32) : "memory");
        asm volatile("st.shared.u32 [%0], %1;" ::"r"(sb + OFF_MISC), "r"((old | 7u) + 1u) : "memory");
        mbar_arrive(sb + BAR_T);
      }
    }
    if (tid == 0) {
      const CUtensorMap* mk = &maps.m[blk * 5 + 1];
      const CUtensorMap* mv = &maps.m[blk * 5 + 2];
      const CUtensorMap* mwq = &maps.m[blk * 5 + 3];
      const CUtensorMap* mwo = &maps.m[blk * 5 + 4];
      const int row0 = (b * 8 + kvh) * 1024;
      uint32_t tstart, t1 = 0, t2 = 0;
      asm volatile("mov.u32 %0, %%globaltimer_lo;" : "=r"(tstart));
      uint64_t pol;
      asm volatile("createpolicy.fractional.L2::evict_first.b64 %0, 1.0;" : "=l"(pol));
      const CUtensorMap* mx = &maps.m[blk * 5 + 0];
      uint32_t st = 2, ph = 0;
#pragma unroll 1
      for (int t = 6; t < 28; t++) {
        if (t == 6) tma3d_pf(mwq, 16 * (6 + b), kvh * 8);
        if (t == 10) tma3d_pf(mwq, 16 * (14 + b), kvh * 8);
        if (t == 14 && b < 6) tma3d_pf(mwq, 16 * (22 + b), kvh * 8);
        if (t >= 18 && t < 26 && !(t & 1)) {
          const int q = (t - 18) >> 1;
          if (q == 0) mbar_expect_tx(sb + BAR_FULL, SLOT_B);
          tma3d_ef(sb + OFF_SLOT + q * 8192, &maps.k8[blk], row0, q, sb + BAR_FULL, pol);
        }
        mbar_wait(sb + BAR_WEMPT + 8 * st, ph);
        const int xc = t - 1;
        const bool hx = xc < 7;
        mbar_expect_tx(sb + BAR_WFULL + 8 * st, hx ? WST_B + 10240 : WST_B);
        tma3d(sb + OFF_W + st * WST_B, mwq, 16 * t, kvh * 8, sb + BAR_WFULL + 8 * st);
        if (hx) tma3d(sb + OFF_Q + xc * 10240, mx, b * 80, xc, sb + BAR_WFULL + 8 * st);
        if (++st == 6) st = 0;
        if (st == 2) ph ^= 1;
      }
      mbar_wait(sb + BAR_WEMPT, 1);
      mbar_wait(sb + BAR_WEMPT + 8, 1);
      mbar_expect_tx(sb + BAR_FULL + 8, SLOT_B);
      tma3d_ef(sb + OFF_SLOT + SLOT_B, mk, row0 + 64, 0, sb + BAR_FULL + 8, pol);
      mbar_wait(sb + BAR_WEMPT + 16, 0);
      mbar_wait(sb + BAR_WEMPT + 24, 0);
#pragma unroll 1
      for (int i = 2; i < 32; i++) {
        uint32_t s, use;
        kv_slot(i, s, use);
        const bool isv = !(i & 1);
        const int j = isv ? ((i - 2) >> 1) : ((i + 1) >> 1);
        if (use > 0) mbar_wait(sb + BAR_EMPTY + 8 * s, (use - 1) & 1);
        {
          uint32_t due = PACE_T0 + i * PACE_TAU, now;
          if (i >= 8) due = max(due, t2 + 2 * PACE_MIN);
          do { asm volatile("mov.u32 %0, %%globaltimer_lo;" : "=r"(now)); } while (now - tstart < due);
          t2 = t1;
          t1 = now - tstart;
        }
        if (i == 31) {
          mbar_expect_tx(sb + BAR_VL, SLOT_B / 2);
          tma3d_ef(sb + OFF_SLOT + s * SLOT_B, &maps.v16[blk], row0 + 960, 0, sb + BAR_VL, pol);
          mbar_expect_tx(sb + BAR_FULL + 8 * s, SLOT_B / 2);
          tma3d_ef(sb + OFF_SLOT + s * SLOT_B + SLOT_B / 2, &maps.v16[blk], row0 + 960, 2, sb + BAR_FULL + 8 * s, pol);
          break;
        }
        mbar_expect_tx(sb + BAR_FULL + 8 * s, SLOT_B);
        tma3d_ef(sb + OFF_SLOT + s * SLOT_B, isv ? mv : mk, row0 + 64 * j, 0, sb + BAR_FULL + 8 * s, pol);
      }
#pragma unroll 1
      for (int u = 0; u < 14; u++) {
        uint32_t s, use;
        wo_slot(u, s, use);
        if (use > 0) mbar_wait(sb + BAR_EMPTY + 8 * s, (use - 1) & 1);
        mbar_expect_tx(sb + BAR_FULL + 8 * s, SLOT_B);
        tma3d(sb + OFF_SLOT + s * SLOT_B, mwo, kvh * 512 + 256 * (u & 1), u >> 1, sb + BAR_FULL + 8 * s);
      }
    }
  } else if (wg == 1) {
    asm volatile("setmaxnreg.dec.sync.aligned.u32 104;");
    nb_sync(0, 480);
    ROLE_IDS();
    float m[5], l[5];
#pragma unroll
    for (int r = 0; r < 5; r++) { m[r] = -INFINITY; l[r] = 0.f; }
    SCtx cx;
    {
      const uint32_t li = lane & 7, lm = lane >> 3;
      cx.pa01 = sb + OFF_P + (16 * wi + li + 8 * (lm & 1)) * 128 + (((lm >> 1) ^ li) << 4);
      cx.pa2 = sb + OFF_P + (128 + 8 * wi + li) * 128 + ((lm ^ li) << 4);
      const uint32_t r8 = lane >> 2;
      cx.sa01 = sb + OFF_SC + (40 * (r8 >> 1) + 2 * (2 * wi) + (r8 & 1)) * 4;
      cx.sa2 = sb + OFF_SC + (40 * (r8 >> 1) + 2 * (16 + wi) + (r8 & 1)) * 4;
      cx.wr = (lane & 3) == 0;
    }
    nb_sync(NB_Q, 384);
#pragma unroll 1
    for (int j = 0; j < 16; j++) s_tile(j, m, l, cx, wi, lane);
#pragma unroll
    for (int r = 0; r < 5; r++) {
      float lr = l[r];
      lr += __shfl_xor_sync(0xffffffffu, lr, 1);
      lr += __shfl_xor_sync(0xffffffffu, lr, 2);
      float inv;
      asm("rcp.approx.ftz.f32 %0, %1;" : "=f"(inv) : "f"(lr));
      if (cx.wr) sts32((r < 4 ? cx.sa01 + (r >> 1) * 64 + (r & 1) * 8 : cx.sa2) + (OFF_LINV - OFF_SC), inv);
    }
    nb_arrive(NB_O2, 384);
    uint32_t tid2, bid2;
    asm volatile("mov.u32 %0, %%tid.x;" : "=r"(tid2));
    asm volatile("mov.u32 %0, %%ctaid.x;" : "=r"(bid2));
    if (tid2 < 160) {
      if (tid2 == 128) {
        uint32_t target, z, it = 0;
        mbar_wait(sb + BAR_T, 0);
        asm volatile("ld.shared.u32 %0, [%1];" : "=r"(target) : "r"(sb + OFF_MISC) : "memory");
        do {
          asm volatile("ld.acquire.gpu.global.u32 %0, [%1];" : "=r"(z) : "l"(g_zero + ((bid2 >> 6) * 8 + (bid2 & 7)) * 32) : "memory");
          if (++it > (1u << 22)) __trap();
        } while ((int)(z - target) < 0);
        asm volatile("fence.proxy.async;" ::: "memory");
      }
#pragma unroll 1
      for (int p = 0; p < 7; p++) {
        nb_sync(NB_SF + (p & 1), 160);
        if (tid2 == 128) {
#pragma unroll
          for (int k = 4; k >= 0; k--) {
            asm volatile("cp.reduce.async.bulk.tensor.3d.global.shared::cta.add.tile.bulk_group [%0, {%1, %2, %3}], [%4];"
                         ::"l"(&maps.o), "r"(0), "r"((bid2 & 7) * 80 + 16 * k), "r"((bid2 >> 6) * 7 + p),
                         "r"(sb + OFF_ST + (k == 4 ? 16384 : (p & 1) * 8192 + k * 2048)) : "memory");
            if (k == 4 || k == 0) asm volatile("cp.async.bulk.commit_group;" ::: "memory");
          }
          asm volatile("cp.async.bulk.wait_group.read 1;" ::: "memory");
        }
        __syncwarp();
        if (p < 6) nb_arrive(nb_se((p + 1) & 1), 160);
        if (tid2 == 128) asm volatile("cp.async.bulk.wait_group.read 0;" ::: "memory");
        __syncwarp();
        if (p < 5) nb_arrive(NB_GO + (p & 1), 160);
      }
    }
  } else {
    asm volatile("setmaxnreg.inc.sync.aligned.u32 192;");
    ROLE_IDS();
    const int w = __shfl_sync(0xffffffffu, (tid >> 7) & 1, 0);
    const uint32_t li = lane & 7, lm = lane >> 3;
    {
      float acc[160];
#pragma unroll
      for (int i = 0; i < 160; i++) acc[i] = 0.f;
      reg_fence<160>(acc);
      nb_sync(0, 480);
      uint32_t st = 2, ph = 0, pst = 0, ok = 0;
#pragma unroll 1
      for (int t = 0; t < 28; t++) {
        if (!ok) mbar_wait(sb + BAR_WFULL + 8 * st, ph);
        const uint32_t nst = (st == 5) ? 0 : st + 1, nph = (nst == 2) ? ph ^ 1 : ph;
        ok = mbar_test(sb + BAR_WFULL + 8 * nst, nph);
        const uint32_t da = dlo(sb + OFF_W) + st * (WST_B >> 4) + w * (8192 >> 4);
        const uint32_t db = dlo(sb + OFF_Q) + (((t >> 2) * 10240 + (t & 3) * 32) >> 4);
        wg_fence();
        static_for<0, 4>([&](auto C) { constexpr int cc = decltype(C)::value; wgmma_n80_mk1<cc * 2048, 0>(acc + 40 * cc, da, db); });
        wg_commit();
        wg_wait<1>();
        if (t > 0 && lane == 0) mbar_arrive(sb + BAR_WEMPT + 8 * pst);
        pst = st;
        st = nst;
        ph = nph;
      }
      wg_wait<0>();
      reg_fence<160>(acc);
      const uint32_t qa = sb + OFF_Q + (80 * w + 8 * (lm >> 1) + li) * 128 + (((2 * wi + (lm & 1)) ^ li) << 4);
#pragma unroll
      for (int cc = 0; cc < 4; cc++) {
        if (cc == 2) nb_sync(NB_O, 256);
#pragma unroll
        for (int jj = 0; jj < 5; jj++) {
          const float* q = acc + 40 * cc + 8 * jj;
          stsm4t(qa + cc * QCHUNK + jj * 2048, pack_bf16(q[0], q[1]), pack_bf16(q[2], q[3]), pack_bf16(q[4], q[5]),
                 pack_bf16(q[6], q[7]));
        }
      }
      fence_async();
      nb_arrive(NB_Q, 384);
    }
    {
    float acc[160];
#pragma unroll
    for (int i = 0; i < 160; i++) acc[i] = 0.f;
    reg_fence<160>(acc);
#pragma unroll 1
    for (int j = 0; j < 16; j++) {
      const uint32_t pb = j & 1;
      nb_sync(NB_PFULL + pb, 384);
      if (j > 0) {
        const float4 f = lds128(sb + OFF_FLAG + pb * 16);
        if ((__float_as_uint(f.x) | __float_as_uint(f.y) | __float_as_uint(f.z) | __float_as_uint(f.w)) != 0) {
          const uint32_t sc = sb + OFF_SC + pb * 640 + (lane & 3) * 160;
#pragma unroll
          for (int g = 0; g < 10; g++) {
            const float4 a = lds128(sc + g * 16);
#pragma unroll
            for (int mb = 0; mb < 2; mb++) {
              float* q = acc + 80 * mb + 8 * g;
              q[0] *= a.x; q[1] *= a.y; q[2] *= a.x; q[3] *= a.y;
              q[4] *= a.z; q[5] *= a.w; q[6] *= a.z; q[7] *= a.w;
            }
          }
        }
      }
      uint32_t slot, use;
      kv_slot(j == 15 ? 31 : 2 * j + 2, slot, use);
      reg_fence<160>(acc);
      if (j < 15) nb_sync(NB_GO, 384);
      else if (w == 1) nb_sync(NB_O, 256);
      if (j == 15 && w == 0) mbar_wait(sb + BAR_VL, 0);
      else mbar_wait(sb + BAR_FULL + 8 * slot, use & 1);
      const uint32_t da = dlo(sb + OFF_SLOT) + slot * (SLOT_B >> 4) + w * (16384 >> 4);
      const uint32_t db = dlo(sb + OFF_P) + pb * (QCHUNK >> 4);
      wg_fence();
      static_for<0, 4>([&](auto K) {
        constexpr int ks = decltype(K)::value;
        wgmma_n160_mk1<ks * 2048, ks * 32>(acc, da, db);
        wgmma_n160_mk1<8192 + ks * 2048, ks * 32>(acc + 80, da, db);
      });
      wg_commit();
      if (j == 15 && w == 0) nb_arrive(NB_O, 256);
      wg_wait<0>();
      reg_fence<160>(acc);
      if (lane == 0) mbar_arrive(sb + BAR_EMPTY + 8 * slot);
      if (j < 14) nb_arrive(NB_PEMPTY + pb, 384);
    }
    {
      const uint32_t oa = sb + OFF_Q + 2 * w * QCHUNK + (8 * (lm >> 1) + li) * 128 + (((2 * wi + (lm & 1)) ^ li) << 4);
#pragma unroll
      for (int mb = 0; mb < 2; mb++)
#pragma unroll
        for (int jj = 0; jj < 10; jj++) {
          const float* q = acc + 80 * mb + 8 * jj;
          stsm4t(oa + mb * QCHUNK + jj * 2048, pack_bf16(q[0], q[1]), pack_bf16(q[2], q[3]), pack_bf16(q[4], q[5]),
                 pack_bf16(q[6], q[7]));
        }
      fence_async();
    }
    }
    nb_sync(NB_O2, 384);
    constexpr uint32_t dob = dlo(sb + OFF_Q);
    const uint32_t sta = sb + OFF_ST + (8 * (lm >> 1) + li) * 128 + (((2 * wi + (lm & 1)) ^ li) << 4);
    float linv[40];
#pragma unroll
    for (int g = 0; g < 10; g++) {
      const float4 f = lds128(sb + OFF_LINV + (lane & 3) * 160 + g * 16);
      linv[4 * g] = f.x; linv[4 * g + 1] = f.y; linv[4 * g + 2] = f.z; linv[4 * g + 3] = f.w;
    }
#pragma unroll 1
    for (int p = w; p < 7; p += 2) {
      float acc[40], acc1[40];
      uint32_t slot0, use0, slot1, use1;
      wo_slot(2 * p, slot0, use0);
      wo_slot(2 * p + 1, slot1, use1);
      mbar_wait(sb + BAR_FULL + 8 * slot0, use0 & 1);
      if (p > 0) nb_sync(NB_ORD + w, 256);
      uint32_t da = dlo(sb + OFF_SLOT) + slot0 * (SLOT_B >> 4);
      wg_fence();
      wgmma_n80_mk_z<0, 0>(acc, da, dob);
      static_for<1, 9>([&](auto K) {
        constexpr int ks = decltype(K)::value;
        wgmma_n80_mk1<ks * 2048, (ks >> 2) * QCHUNK + (ks & 3) * 32>(acc, da, dob);
      });
      const uint32_t ok1 = mbar_test(sb + BAR_FULL + 8 * slot1, use1 & 1);
      static_for<9, 16>([&](auto K) {
        constexpr int ks = decltype(K)::value;
        wgmma_n80_mk1<ks * 2048, (ks >> 2) * QCHUNK + (ks & 3) * 32>(acc, da, dob);
      });
      wg_commit();
      if (!ok1) mbar_wait(sb + BAR_FULL + 8 * slot1, use1 & 1);
      da = dlo(sb + OFF_SLOT) + slot1 * (SLOT_B >> 4);
      wg_fence();
      wgmma_n80_mk_z<0, 10240>(acc1, da, dob);
      static_for<1, 6>([&](auto K) {
        constexpr int ks = decltype(K)::value;
        wgmma_n80_mk1<ks * 2048, 10240 + (ks >> 2) * QCHUNK + (ks & 3) * 32>(acc1, da, dob);
      });
      wg_commit();
      wg_wait<1>();
      if (lane == 0) mbar_arrive_n(sb + BAR_EMPTY + 8 * slot0, 2);
      wg_fence();
      static_for<6, 16>([&](auto K) {
        constexpr int ks = decltype(K)::value;
        wgmma_n80_mk1<ks * 2048, 10240 + (ks >> 2) * QCHUNK + (ks & 3) * 32>(acc1, da, dob);
      });
      wg_commit();
      if (p < 6) nb_arrive(NB_ORD + (w ^ 1), 256);
      wg_wait<0>();
      reg_fence<40>(acc);
      reg_fence<40>(acc1);
      if (lane == 0) mbar_arrive_n(sb + BAR_EMPTY + 8 * slot1, 2);
#pragma unroll
      for (int i = 0; i < 40; i++)
        acc[i] = fmaf(acc[i], linv[2 * (i >> 2) + (i & 1)], acc1[i] * linv[20 + 2 * (i >> 2) + (i & 1)]);
      uint32_t pk[20];
#pragma unroll
      for (int i = 0; i < 20; i++) pk[i] = pack_bf16(acc[2 * i], acc[2 * i + 1]);
      if (p > 1) nb_sync(NB_GO + w, 160);
#pragma unroll
      for (int k = 0; k < 4; k++) stsm4t(sta + w * 8192 + k * 2048, pk[4 * k], pk[4 * k + 1], pk[4 * k + 2], pk[4 * k + 3]);
      if (p > 0) nb_sync(nb_se(w), 160);
      stsm4t(sta + 16384, pk[16], pk[17], pk[18], pk[19]);
      fence_async();
      nb_arrive(NB_SF + w, 160);
    }
  }
}

typedef CUresult (*EncodeFn)(CUtensorMap*, CUtensorMapDataType, cuuint32_t, void*, const cuuint64_t*, const cuuint64_t*,
                             const cuuint32_t*, const cuuint32_t*, CUtensorMapInterleave, CUtensorMapSwizzle,
                             CUtensorMapL2promotion, CUtensorMapFloatOOBfill);

void encode3d(EncodeFn enc, CUtensorMap* m, void* p, uint64_t rows, uint64_t cols, uint32_t box_rows,
              uint32_t box_blocks) {
  cuuint64_t dims[3] = {64, rows, cols / 64};
  cuuint64_t strides[2] = {cols * 2, 128};
  cuuint32_t box[3] = {64, box_rows, box_blocks};
  cuuint32_t es[3] = {1, 1, 1};
  enc(m, CU_TENSOR_MAP_DATA_TYPE_BFLOAT16, 3, p, dims, strides, box, es, CU_TENSOR_MAP_INTERLEAVE_NONE,
      CU_TENSOR_MAP_SWIZZLE_128B,
      cols == 256 ? CU_TENSOR_MAP_L2_PROMOTION_L2_256B : CU_TENSOR_MAP_L2_PROMOTION_L2_128B,
      CU_TENSOR_MAP_FLOAT_OOB_FILL_NONE);
}

}

extern "C" void kernel_launch(void* const* d_in, const int* in_sizes, int n_in, void* d_out, int out_size) {
  static EncodeFn enc = nullptr;
  if (!enc) {
    void* fn = nullptr;
    cudaDriverEntryPointQueryResult qr;
    cudaGetDriverEntryPoint("cuTensorMapEncodeTiled", &fn, cudaEnableDefault, &qr);
    enc = (EncodeFn)fn;
    cudaFuncSetAttribute(fused_gqa_kernel, cudaFuncAttributeMaxDynamicSharedMemorySize, SMEM_BYTES);
  }
  Maps maps;
  for (int blk = 0; blk < 2; blk++) {
    encode3d(enc, &maps.m[blk * 5 + 0], d_in[blk * 5 + 0], 640, 448, 80, 1);
    encode3d(enc, &maps.m[blk * 5 + 1], d_in[blk * 5 + 1], 65536, 256, 64, 4);
    encode3d(enc, &maps.m[blk * 5 + 2], d_in[blk * 5 + 2], 65536, 256, 64, 4);
    encode3d(enc, &maps.m[blk * 5 + 3], d_in[blk * 5 + 3], 448, 4096, 16, 8);
    encode3d(enc, &maps.m[blk * 5 + 4], d_in[blk * 5 + 4], 4096, 448, 256, 1);
    encode3d(enc, &maps.k8[blk], d_in[blk * 5 + 1], 65536, 256, 64, 1);
    encode3d(enc, &maps.v16[blk], d_in[blk * 5 + 2], 65536, 256, 64, 2);
  }
  encode3d(enc, &maps.o, d_out, 640, 896, 16, 1);
  fused_gqa_kernel<<<NCTA, NTHREADS, SMEM_BYTES>>>(maps, (__nv_bfloat16*)d_out);
}
```

```cpp
#include <cuda_runtime.h>
#include <cuda_bf16.h>
#include <cuda.h>
#include <stdint.h>

namespace {

constexpr int NCTA = 128;
constexpr int NTHREADS = 512;

constexpr uint32_t SB = 0x400;
constexpr uint32_t OFF_Q     = 0;
constexpr uint32_t QCHUNK    = 20480;
constexpr uint32_t OFF_SLOT  = 81920;
constexpr uint32_t SLOT_B    = 32768;
constexpr uint32_t OFF_P     = OFF_SLOT + 3 * SLOT_B;
constexpr uint32_t OFF_W     = OFF_SLOT + SLOT_B;
constexpr uint32_t WST_B     = 16384;
constexpr uint32_t OFF_SC    = OFF_P + 2 * QCHUNK;
constexpr uint32_t OFF_FLAG  = OFF_SC + 1280;
constexpr uint32_t OFF_LINV  = OFF_FLAG + 32;
constexpr uint32_t OFF_ST    = OFF_P + SLOT_B;
constexpr uint32_t OFF_ML    = OFF_ST + 10240;
constexpr uint32_t OFF_BAR   = OFF_ST + 18432;
constexpr uint32_t BAR_FULL  = OFF_BAR;
constexpr uint32_t BAR_EMPTY = BAR_FULL + 32;
constexpr uint32_t BAR_WFULL = BAR_EMPTY + 32;
constexpr uint32_t BAR_WEMPT = BAR_WFULL + 48;
constexpr uint32_t BAR_T     = BAR_WEMPT + 48;
constexpr uint32_t BAR_VL    = BAR_T + 8;
constexpr uint32_t BAR_K0    = BAR_VL + 8;
constexpr uint32_t OFF_MISC  = BAR_K0 + 8;
constexpr uint32_t SMEM_BYTES = OFF_MISC + 16;

#define PACE_TAU 1345
#define PACE_T0 2800
#define PACE_MIN 1250

struct Maps {
  CUtensorMap m[10];
  CUtensorMap k8[2];
  CUtensorMap v16[2];
  CUtensorMap o;
};

__device__ unsigned int g_zero[16 * 32];

__device__ __forceinline__ void mbar_init(uint32_t bar, uint32_t cnt) {
  asm volatile("mbarrier.init.shared::cta.b64 [%0], %1;" ::"r"(bar), "r"(cnt) : "memory");
}
__device__ __forceinline__ void mbar_expect_tx(uint32_t bar, uint32_t bytes) {
  asm volatile("mbarrier.arrive.expect_tx.shared::cta.b64 _, [%0], %1;" ::"r"(bar), "r"(bytes) : "memory");
}
__device__ __forceinline__ void mbar_arrive(uint32_t bar) {
  asm volatile("mbarrier.arrive.shared::cta.b64 _, [%0];" ::"r"(bar) : "memory");
}
__device__ __forceinline__ void mbar_arrive_n(uint32_t bar, uint32_t n) {
  asm volatile("mbarrier.arrive.shared::cta.b64 _, [%0], %1;" ::"r"(bar), "r"(n) : "memory");
}
__device__ __forceinline__ void mbar_wait(uint32_t bar, uint32_t parity) {
  asm volatile(
      "{\n.reg .pred p;\n.reg .u32 c;\nmov.u32 c, 0;\n"
      "W_LOOP:\n"
      "mbarrier.try_wait.parity.shared::cta.b64 p, [%0], %1;\n"
      "@p bra W_DONE;\n"
      "add.u32 c, c, 1;\n"
      "setp.lt.u32 p, c, 0x80000;\n"
      "@p bra W_LOOP;\n"
      "trap;\n"
      "W_DONE:\n}\n" ::"r"(bar), "r"(parity) : "memory");
}
__device__ __forceinline__ uint32_t mbar_test(uint32_t bar, uint32_t parity) {
  uint32_t ok;
  asm volatile("{\n.reg .pred p;\nmbarrier.test_wait.parity.shared::cta.b64 p, [%1], %2;\nselp.u32 %0, 1, 0, p;\n}\n"
               : "=r"(ok) : "r"(bar), "r"(parity) : "memory");
  return ok;
}
__device__ __forceinline__ void nb_sync(uint32_t id, uint32_t n) { asm volatile("bar.sync %0, %1;" ::"r"(id), "r"(n) : "memory"); }
__device__ __forceinline__ void nb_arrive(uint32_t id, uint32_t n) { asm volatile("bar.arrive %0, %1;" ::"r"(id), "r"(n) : "memory"); }
constexpr uint32_t NB_O = 1, NB_PFULL = 2, NB_PEMPTY = 4, NB_GO = 6, NB_Q = 8, NB_ORD = 10, NB_O2 = 12, NB_S = 13, NB_SF = 14;
__device__ __forceinline__ uint32_t nb_se(uint32_t w) { return w ? NB_S : NB_Q; }
__device__ __forceinline__ void tma3d(uint32_t dst, const CUtensorMap* m, int c1, int c2, uint32_t bar) {
  asm volatile(
      "cp.async.bulk.tensor.3d.shared::cluster.global.mbarrier::complete_tx::bytes [%0], [%1, {%2, %3, %4}], [%5];"
      ::"r"(dst), "l"(m), "r"(0), "r"(c1), "r"(c2), "r"(bar) : "memory");
}
__device__ __forceinline__ void tma3d_ef(uint32_t dst, const CUtensorMap* m, int c1, int c2, uint32_t bar, uint64_t pol) {
  asm volatile(
      "cp.async.bulk.tensor.3d.shared::cluster.global.mbarrier::complete_tx::bytes.L2::cache_hint [%0], [%1, {%2, %3, %4}], [%5], %6;"
      ::"r"(dst), "l"(m), "r"(0), "r"(c1), "r"(c2), "r"(bar), "l"(pol) : "memory");
}
__device__ __forceinline__ void tma3d_pf(const CUtensorMap* m, int c1, int c2) {
  asm volatile("cp.async.bulk.prefetch.tensor.3d.L2.global [%0, {%1, %2, %3}];" ::"l"(m), "r"(0), "r"(c1), "r"(c2)
               : "memory");
}
__device__ __forceinline__ void wg_fence() { asm volatile("wgmma.fence.sync.aligned;" ::: "memory"); }
__device__ __forceinline__ void wg_commit() { asm volatile("wgmma.commit_group.sync.aligned;" ::: "memory"); }
template <int N>
__device__ __forceinline__ void wg_wait() { asm volatile("wgmma.wait_group.sync.aligned %0;" ::"n"(N) : "memory"); }
__device__ __forceinline__ void fence_async() { asm volatile("fence.proxy.async.shared::cta;" ::: "memory"); }
template <int N>
__device__ __forceinline__ void reg_fence(float* d) {
#pragma unroll
  for (int i = 0; i < N; i++) asm volatile("" : "+f"(d[i])::"memory");
}
__device__ __forceinline__ constexpr uint32_t dlo(uint32_t saddr) { return ((saddr & 0x3FFFFu) >> 4) | (1u << 16); }
template <int V>
struct IC { static constexpr int value = V; };
template <int I, int N, class F>
__device__ __forceinline__ void static_for(F&& f) {
  if constexpr (I < N) {
    f(IC<I>{});
    static_for<I + 1, N>(f);
  }
}
__device__ __forceinline__ uint32_t pack_bf16(float lo, float hi) {
  uint32_t r;
  asm("cvt.rn.bf16x2.f32 %0, %1, %2;" : "=r"(r) : "f"(hi), "f"(lo));
  return r;
}
template <uint32_t XR, uint32_t OFF>
__device__ __forceinline__ void stsm4_o(uint32_t a, uint32_t r0, uint32_t r1, uint32_t r2, uint32_t r3) {
  asm volatile("{\n.reg .b32 t;\nxor.b32 t, %0, %6;\nstmatrix.sync.aligned.m8n8.x4.shared.b16 [t + %5], {%1, %2, %3, %4};\n}\n"
               ::"r"(a), "r"(r0), "r"(r1), "r"(r2), "r"(r3), "n"(OFF), "n"(XR) : "memory");
}
__device__ __forceinline__ void stsm4t(uint32_t a, uint32_t r0, uint32_t r1, uint32_t r2, uint32_t r3) {
  asm volatile("stmatrix.sync.aligned.m8n8.x4.trans.shared.b16 [%0], {%1, %2, %3, %4};" ::"r"(a), "r"(r0), "r"(r1),
               "r"(r2), "r"(r3) : "memory");
}
__device__ __forceinline__ float ex2(float x) {
  float y;
  asm("ex2.approx.ftz.f32 %0, %1;" : "=f"(y) : "f"(x));
  return y;
}
__device__ __forceinline__ float4 lds128(uint32_t a) {
  float4 v;
  asm volatile("ld.shared.v4.f32 {%0, %1, %2, %3}, [%4];" : "=f"(v.x), "=f"(v.y), "=f"(v.z), "=f"(v.w) : "r"(a) : "memory");
  return v;
}
__device__ __forceinline__ void sts32(uint32_t a, float v) {
  asm volatile("st.shared.f32 [%0], %1;" ::"r"(a), "f"(v) : "memory");
}
template <uint32_t OA, uint32_t OB, uint32_t HIA = 0x40000040u>
__device__ __forceinline__ void wgmma_n64_kk_z(float* d, uint32_t a, uint32_t b) {
  asm volatile(
      "{\n.reg .b32 ta, tb;\n.reg .b64 da, db;\nadd.u32 ta, %32, %34;\nadd.u32 tb, %33, %35;\nmov.b64 da, {ta, %36};\nmov.b64 db, {tb, 0x40000040};\n"
      "wgmma.mma_async.sync.aligned.m64n64k16.f32.bf16.bf16 {"
      "%0, %1, %2, %3, %4, %5, %6, %7, %8, %9, %10, %11, %12, %13, %14, %15,"
      "%16, %17, %18, %19, %20, %21, %22, %23, %24, %25, %26, %27, %28, %29, %30, %31}, da, db, 0, 1, 1, 0, 0;\n}\n"
      : "=f"(d[0]), "=f"(d[1]), "=f"(d[2]), "=f"(d[3]), "=f"(d[4]), "=f"(d[5]), "=f"(d[6]), "=f"(d[7]),
        "=f"(d[8]), "=f"(d[9]), "=f"(d[10]), "=f"(d[11]), "=f"(d[12]), "=f"(d[13]), "=f"(d[14]), "=f"(d[15]),
        "=f"(d[16]), "=f"(d[17]), "=f"(d[18]), "=f"(d[19]), "=f"(d[20]), "=f"(d[21]), "=f"(d[22]), "=f"(d[23]),
        "=f"(d[24]), "=f"(d[25]), "=f"(d[26]), "=f"(d[27]), "=f"(d[28]), "=f"(d[29]), "=f"(d[30]), "=f"(d[31])
      : "r"(a), "r"(b), "n"(OA >> 4), "n"(OB >> 4), "n"(HIA));
}

template <uint32_t OA, uint32_t OB, uint32_t HIA = 0x40000040u>
__device__ __forceinline__ void wgmma_n64_kk(float* d, uint32_t a, uint32_t b) {
  asm volatile(
      "{\n.reg .b32 ta, tb;\n.reg .b64 da, db;\nadd.u32 ta, %32, %34;\nadd.u32 tb, %33, %35;\nmov.b64 da, {ta, %36};\nmov.b64 db, {tb, 0x40000040};\n"
      "wgmma.mma_async.sync.aligned.m64n64k16.f32.bf16.bf16 {"
      "%0, %1, %2, %3, %4, %5, %6, %7, %8, %9, %10, %11, %12, %13, %14, %15,"
      "%16, %17, %18, %19, %20, %21, %22, %23, %24, %25, %26, %27, %28, %29, %30, %31}, da, db, 1, 1, 1, 0, 0;\n}\n"
      : "+f"(d[0]), "+f"(d[1]), "+f"(d[2]), "+f"(d[3]), "+f"(d[4]), "+f"(d[5]), "+f"(d[6]), "+f"(d[7]),
        "+f"(d[8]), "+f"(d[9]), "+f"(d[10]), "+f"(d[11]), "+f"(d[12]), "+f"(d[13]), "+f"(d[14]), "+f"(d[15]),
        "+f"(d[16]), "+f"(d[17]), "+f"(d[18]), "+f"(d[19]), "+f"(d[20]), "+f"(d[21]), "+f"(d[22]), "+f"(d[23]),
        "+f"(d[24]), "+f"(d[25]), "+f"(d[26]), "+f"(d[27]), "+f"(d[28]), "+f"(d[29]), "+f"(d[30]), "+f"(d[31])
      : "r"(a), "r"(b), "n"(OA >> 4), "n"(OB >> 4), "n"(HIA));
}

template <uint32_t OA, uint32_t OB, uint32_t HIA = 0x40000040u>
__device__ __forceinline__ void wgmma_n80_mk_z(float* d, uint32_t a, uint32_t b) {
  asm volatile(
      "{\n.reg .b32 ta, tb;\n.reg .b64 da, db;\nadd.u32 ta, %40, %42;\nadd.u32 tb, %41, %43;\nmov.b64 da, {ta, %44};\nmov.b64 db, {tb, 0x40000040};\n"
      "wgmma.mma_async.sync.aligned.m64n80k16.f32.bf16.bf16 {"
      "%0, %1, %2, %3, %4, %5, %6, %7, %8, %9, %10, %11, %12, %13, %14, %15,"
      "%16, %17, %18, %19, %20, %21, %22, %23, %24, %25, %26, %27, %28, %29, %30, %31,"
      "%32, %33, %34, %35, %36, %37, %38, %39}, da, db, 0, 1, 1, 1, 0;\n}\n"
      : "=f"(d[0]), "=f"(d[1]), "=f"(d[2]), "=f"(d[3]), "=f"(d[4]), "=f"(d[5]), "=f"(d[6]), "=f"(d[7]),
        "=f"(d[8]), "=f"(d[9]), "=f"(d[10]), "=f"(d[11]), "=f"(d[12]), "=f"(d[13]), "=f"(d[14]), "=f"(d[15]),
        "=f"(d[16]), "=f"(d[17]), "=f"(d[18]), "=f"(d[19]), "=f"(d[20]), "=f"(d[21]), "=f"(d[22]), "=f"(d[23]),
        "=f"(d[24]), "=f"(d[25]), "=f"(d[26]), "=f"(d[27]), "=f"(d[28]), "=f"(d[29]), "=f"(d[30]), "=f"(d[31]),
        "=f"(d[32]), "=f"(d[33]), "=f"(d[34]), "=f"(d[35]), "=f"(d[36]), "=f"(d[37]), "=f"(d[38]), "=f"(d[39])
      : "r"(a), "r"(b), "n"(OA >> 4), "n"(OB >> 4), "n"(HIA));
}

template <uint32_t OA, uint32_t OB, uint32_t HIA = 0x40000040u>
__device__ __forceinline__ void wgmma_n80_mk1(float* d, uint32_t a, uint32_t b) {
  asm volatile(
      "{\n.reg .b32 ta, tb;\n.reg .b64 da, db;\nadd.u32 ta, %40, %42;\nadd.u32 tb, %41, %43;\nmov.b64 da, {ta, %44};\nmov.b64 db, {tb, 0x40000040};\n"
      "wgmma.mma_async.sync.aligned.m64n80k16.f32.bf16.bf16 {"
      "%0, %1, %2, %3, %4, %5, %6, %7, %8, %9, %10, %11, %12, %13, %14, %15,"
      "%16, %17, %18, %19, %20, %21, %22, %23, %24, %25, %26, %27, %28, %29, %30, %31,"
      "%32, %33, %34, %35, %36, %37, %38, %39}, da, db, 1, 1, 1, 1, 0;\n}\n"
      : "+f"(d[0]), "+f"(d[1]), "+f"(d[2]), "+f"(d[3]), "+f"(d[4]), "+f"(d[5]), "+f"(d[6]), "+f"(d[7]),
        "+f"(d[8]), "+f"(d[9]), "+f"(d[10]), "+f"(d[11]), "+f"(d[12]), "+f"(d[13]), "+f"(d[14]), "+f"(d[15]),
        "+f"(d[16]), "+f"(d[17]), "+f"(d[18]), "+f"(d[19]), "+f"(d[20]), "+f"(d[21]), "+f"(d[22]), "+f"(d[23]),
        "+f"(d[24]), "+f"(d[25]), "+f"(d[26]), "+f"(d[27]), "+f"(d[28]), "+f"(d[29]), "+f"(d[30]), "+f"(d[31]),
        "+f"(d[32]), "+f"(d[33]), "+f"(d[34]), "+f"(d[35]), "+f"(d[36]), "+f"(d[37]), "+f"(d[38]), "+f"(d[39])
      : "r"(a), "r"(b), "n"(OA >> 4), "n"(OB >> 4), "n"(HIA));
}

template <uint32_t OA, uint32_t OB, uint32_t HIA = 0x40000040u>
__device__ __forceinline__ void wgmma_n160_mk1(float* d, uint32_t a, uint32_t b) {
  asm volatile(
      "{\n.reg .b32 ta, tb;\n.reg .b64 da, db;\nadd.u32 ta, %80, %82;\nadd.u32 tb, %81, %83;\nmov.b64 da, {ta, %84};\nmov.b64 db, {tb, 0x40000040};\n"
      "wgmma.mma_async.sync.aligned.m64n160k16.f32.bf16.bf16 {"
      "%0, %1, %2, %3, %4, %5, %6, %7, %8, %9, %10, %11, %12, %13, %14, %15,"
      "%16, %17, %18, %19, %20, %21, %22, %23, %24, %25, %26, %27, %28, %29, %30, %31,"
      "%32, %33, %34, %35, %36, %37, %38, %39, %40, %41, %42, %43, %44, %45, %46, %47,"
      "%48, %49, %50, %51, %52, %53, %54, %55, %56, %57, %58, %59, %60, %61, %62, %63,"
      "%64, %65, %66, %67, %68, %69, %70, %71, %72, %73, %74, %75, %76, %77, %78, %79}, da, db, 1, 1, 1, 1, 0;\n}\n"
      : "+f"(d[0]), "+f"(d[1]), "+f"(d[2]), "+f"(d[3]), "+f"(d[4]), "+f"(d[5]), "+f"(d[6]), "+f"(d[7]),
        "+f"(d[8]), "+f"(d[9]), "+f"(d[10]), "+f"(d[11]), "+f"(d[12]), "+f"(d[13]), "+f"(d[14]), "+f"(d[15]),
        "+f"(d[16]), "+f"(d[17]), "+f"(d[18]), "+f"(d[19]), "+f"(d[20]), "+f"(d[21]), "+f"(d[22]), "+f"(d[23]),
        "+f"(d[24]), "+f"(d[25]), "+f"(d[26]), "+f"(d[27]), "+f"(d[28]), "+f"(d[29]), "+f"(d[30]), "+f"(d[31]),
        "+f"(d[32]), "+f"(d[33]), "+f"(d[34]), "+f"(d[35]), "+f"(d[36]), "+f"(d[37]), "+f"(d[38]), "+f"(d[39]),
        "+f"(d[40]), "+f"(d[41]), "+f"(d[42]), "+f"(d[43]), "+f"(d[44]), "+f"(d[45]), "+f"(d[46]), "+f"(d[47]),
        "+f"(d[48]), "+f"(d[49]), "+f"(d[50]), "+f"(d[51]), "+f"(d[52]), "+f"(d[53]), "+f"(d[54]), "+f"(d[55]),
        "+f"(d[56]), "+f"(d[57]), "+f"(d[58]), "+f"(d[59]), "+f"(d[60]), "+f"(d[61]), "+f"(d[62]), "+f"(d[63]),
        "+f"(d[64]), "+f"(d[65]), "+f"(d[66]), "+f"(d[67]), "+f"(d[68]), "+f"(d[69]), "+f"(d[70]), "+f"(d[71]),
        "+f"(d[72]), "+f"(d[73]), "+f"(d[74]), "+f"(d[75]), "+f"(d[76]), "+f"(d[77]), "+f"(d[78]), "+f"(d[79])
      : "r"(a), "r"(b), "n"(OA >> 4), "n"(OB >> 4), "n"(HIA));
}

__device__ __forceinline__ void kv_slot(int i, uint32_t& slot, uint32_t& use) {
  use = (uint32_t)i / 3u;
  slot = (uint32_t)i - use * 3u;
}
__device__ __forceinline__ void wo_slot(int u, uint32_t& slot, uint32_t& use) {
  uint32_t r = u & 3, q = u >> 2;
  slot = (r == 0) ? 2u : (r == 3) ? 3u : (r - 1u);
  use = q + ((r == 0) ? 10u : (r == 3) ? 0u : 11u);
}

struct SCtx {
  uint32_t pa01, pa2, sa01, sa2;
  bool wr;
};

template <int BLK>
__device__ __forceinline__ void qk_issue(float* s, uint32_t dk, uint32_t qoff = 0) {
  const uint32_t dq = dlo(SB + OFF_Q + BLK * 8192) + qoff;
  constexpr uint32_t HI = (BLK == 2) ? 0x40000020u : 0x40000040u;
  wg_fence();
  constexpr uint32_t T = BLK << 20;
  wgmma_n64_kk_z<0, T, HI>(s, dq, dk);
  static_for<1, 16>([&](auto I) {
    constexpr int ks = decltype(I)::value;
    wgmma_n64_kk<(ks >> 2) * QCHUNK + (ks & 3) * 32, T + (ks >> 2) * 8192 + (ks & 3) * 32, HI>(s, dq, dk);
  });
  wg_commit();
}

template <int BLK, class F>
__device__ __forceinline__ void softmax_blk(float* s, float* mc, float* l, uint32_t& flag, const SCtx& cx, F&& mid) {
  constexpr float c = 0.0625f * 1.4426950408889634f;
  constexpr int NR = (BLK == 2) ? 1 : 2;
  float mx[NR], alpha[NR];
  bool need = false;
#pragma unroll
  for (int r = 0; r < NR; r++) {
    float v0 = fmaxf(s[2 * r], s[2 * r + 1]), v1 = fmaxf(s[2 * r + 4], s[2 * r + 5]);
#pragma unroll
    for (int g = 2; g < 8; g += 2) {
      v0 = fmaxf(v0, fmaxf(s[2 * r + 4 * g], s[2 * r + 4 * g + 1]));
      v1 = fmaxf(v1, fmaxf(s[2 * r + 4 * g + 4], s[2 * r + 4 * g + 5]));
    }
    mx[r] = fmaxf(v0, v1) * c;
    need |= !(mx[r] - mc[2 * BLK + r] <= 8.f);
    alpha[r] = 1.f;
  }
  if (__any_sync(0xffffffffu, need)) {
#pragma unroll
    for (int r = 0; r < NR; r++) mx[r] = fmaxf(mx[r], __shfl_xor_sync(0xffffffffu, mx[r], 1));
#pragma unroll
    for (int r = 0; r < NR; r++) mx[r] = fmaxf(mx[r], __shfl_xor_sync(0xffffffffu, mx[r], 2));
#pragma unroll
    for (int r = 0; r < NR; r++) {
      const float mo = mc[2 * BLK + r];
      const float mn = fmaxf(mo, mx[r]);
      alpha[r] = ex2(mo - mn);
      mc[2 * BLK + r] = mn;
      l[2 * BLK + r] *= alpha[r];
    }
    flag = 1;
  }
#pragma unroll
  for (int r = 0; r < NR; r++) {
    const float nm = -mc[2 * BLK + r];
    float sum0 = l[2 * BLK + r], sum1 = 0.f;
#pragma unroll
    for (int g = 0; g < 8; g++) {
      const float p0 = ex2(fmaf(s[2 * r + 4 * g], c, nm));
      const float p1 = ex2(fmaf(s[2 * r + 4 * g + 1], c, nm));
      s[2 * r + 4 * g] = p0;
      s[2 * r + 4 * g + 1] = p1;
      sum0 += p0;
      sum1 += p1;
    }
    const float lr = sum0 + sum1;
    l[2 * BLK + r] = lr;
    alpha[r] = fmaf(lr, 0.f, alpha[r]);
    if (r == 0) mid();
  }
  if (BLK < 2) {
    static_for<0, 4>([&](auto G) {
      constexpr int g = decltype(G)::value;
      const float* q = s + g * 8;
      stsm4_o<(g << 5), BLK * 8192>(cx.pa01, pack_bf16(q[0], q[1]), pack_bf16(q[2], q[3]), pack_bf16(q[4], q[5]),
                                    pack_bf16(q[6], q[7]));
    });
    if (cx.wr) {
      sts32(cx.sa01 + BLK * 64, alpha[0]);
      sts32(cx.sa01 + BLK * 64 + 8, alpha[NR - 1]);
    }
  } else {
    static_for<0, 2>([&](auto G) {
      constexpr int g = decltype(G)::value;
      const float* q = s + g * 16;
      stsm4_o<(g << 6), 0>(cx.pa2, pack_bf16(q[0], q[1]), pack_bf16(q[4], q[5]), pack_bf16(q[8], q[9]),
                           pack_bf16(q[12], q[13]));
    });
    if (cx.wr) sts32(cx.sa2, alpha[0]);
  }
}

__device__ __forceinline__ void s_tile(int j, float* mc, float* l, SCtx& cx, int wi, int lane) {
  constexpr uint32_t sb = SB;
  float sX[32], sY[32];
  uint32_t flag = 0, slot, use;
  const uint32_t pb = j & 1;
  kv_slot(2 * j - 1, slot, use);
  mbar_wait(sb + BAR_FULL + 8 * slot, use & 1);
  const uint32_t dk = dlo(sb + OFF_SLOT) + slot * (SLOT_B >> 4);
  qk_issue<2>(sX, dk);
  qk_issue<0>(sY, dk);
  if (j >= 2) nb_sync(NB_PEMPTY + pb, 384);
  wg_wait<1>();
  reg_fence<32>(sX);
  softmax_blk<2>(sX, mc, l, flag, cx, [] {});
  qk_issue<1>(sX, dk);
  if (j == 1) nb_sync(NB_S, 384);
  nb_arrive(NB_GO, 384);
  if (j == 1) {
    const float4 a = lds128(sb + OFF_ML + (wi * 32 + lane) * 16), bq = lds128(sb + OFF_ML + 2048 + (wi * 32 + lane) * 16);
    mc[0] = a.x; mc[1] = a.y; l[0] = a.z; l[1] = a.w;
    mc[2] = bq.x; mc[3] = bq.y; l[2] = bq.z; l[3] = bq.w;
  }
  wg_wait<1>();
  reg_fence<32>(sY);
  softmax_blk<0>(sY, mc, l, flag, cx, [&] {
    wg_wait<0>();
    if (lane == 0) mbar_arrive_n(sb + BAR_EMPTY + 8 * slot, 2);
  });
  reg_fence<32>(sX);
  softmax_blk<1>(sX, mc, l, flag, cx, [] {});
  if (lane == 0) asm volatile("st.shared.u32 [%0], %1;" ::"r"(sb + OFF_FLAG + pb * 16 + wi * 4), "r"(flag) : "memory");
  fence_async();
  nb_arrive(NB_PFULL + pb, 384);
  const uint32_t dp = pb ? (0u - QCHUNK) : QCHUNK, ds = pb ? (0u - 640u) : 640u;
  cx.pa01 += dp; cx.pa2 += dp; cx.sa01 += ds; cx.sa2 += ds;
}

__global__ void __launch_bounds__(NTHREADS, 1)
fused_gqa_kernel(const __grid_constant__ Maps maps, __nv_bfloat16* __restrict__ out) {
  extern __shared__ uint8_t smem_raw[];
  constexpr uint32_t sb = SB;
  if ((uint32_t)__cvta_generic_to_shared(smem_raw) != sb) __trap();
  const int wg = __shfl_sync(0xffffffffu, threadIdx.x >> 7, 0);
#define ROLE_IDS()                                                   \
  int tid, bid;                                                      \
  asm volatile("mov.u32 %0, %%tid.x;" : "=r"(tid));                  \
  asm volatile("mov.u32 %0, %%ctaid.x;" : "=r"(bid));                \
  const int wi = __shfl_sync(0xffffffffu, (tid >> 5) & 3, 0);        \
  const int lane = tid & 31;                                         \
  const int blk = bid >> 6, kvh = (bid >> 3) & 7, b = bid & 7;       \
  (void)wi; (void)lane; (void)blk; (void)kvh; (void)b

  if (threadIdx.x == 0) {
    for (int s = 0; s < 4; s++) {
      mbar_init(sb + BAR_FULL + 8 * s, 1);
      mbar_init(sb + BAR_EMPTY + 8 * s, 8);
    }
    for (int s = 0; s < 6; s++) {
      mbar_init(sb + BAR_WFULL + 8 * s, 1);
      mbar_init(sb + BAR_WEMPT + 8 * s, 8);
    }
    mbar_init(sb + BAR_T, 1);
    mbar_init(sb + BAR_VL, 1);
    mbar_init(sb + BAR_K0, 12);
    asm volatile("fence.mbarrier_init.release.cluster;" ::: "memory");
    fence_async();
  }
  if (threadIdx.x < 32) {
    nb_arrive(0, 480);
    nb_arrive(15, 64);
    if (threadIdx.x == 0) {
      const int blk = blockIdx.x >> 6, kvh = (blockIdx.x >> 3) & 7, b = blockIdx.x & 7;
      const CUtensorMap* mx0 = &maps.m[blk * 5 + 0];
      const CUtensorMap* mw0 = &maps.m[blk * 5 + 3];
      static_for<0, 2>([&](auto T) {
        constexpr int t = decltype(T)::value, st = (t + 2) % 6, xc = t ? t - 1 : 0;
        constexpr bool hx = (t == 0) || (xc >= 1);
        mbar_expect_tx(sb + BAR_WFULL + 8 * st, hx ? WST_B + 10240 : WST_B);
        if constexpr (t == 0) tma3d(sb + OFF_Q, mx0, b * 80, 0, sb + BAR_WFULL + 8 * st);
        tma3d(sb + OFF_W + st * WST_B, mw0, 16 * t, kvh * 8, sb + BAR_WFULL + 8 * st);
        if constexpr (t > 0 && hx) tma3d(sb + OFF_Q + xc * 10240, mx0, b * 80, xc, sb + BAR_WFULL + 8 * st);
      });
    }
    __syncwarp();
  }

  if (wg == 0) {
    asm volatile("setmaxnreg.dec.sync.aligned.u32 24;");
    ROLE_IDS();
    if (wi == 1) nb_sync(15, 64);
    if (wi > 1) nb_sync(0, 480);
    if (tid == 32) {
      const CUtensorMap* mx0 = &maps.m[blk * 5 + 0];
      const CUtensorMap* mw0 = &maps.m[blk * 5 + 3];
      static_for<2, 6>([&](auto T) {
        constexpr int t = decltype(T)::value, st = (t + 2) % 6, xc = t - 1;
        constexpr bool hx = (xc >= 1);
        mbar_expect_tx(sb + BAR_WFULL + 8 * st, hx ? WST_B + 10240 : WST_B);
        tma3d(sb + OFF_W + st * WST_B, mw0, 16 * t, kvh * 8, sb + BAR_WFULL + 8 * st);
        if constexpr (hx) tma3d(sb + OFF_Q + xc * 10240, mx0, b * 80, xc, sb + BAR_WFULL + 8 * st);
      });
    }
    if (tid >= 64 && tid < 70) {
      const CUtensorMap* m = (tid == 64) ? &maps.k8[blk] : (tid == 68) ? &maps.v16[blk] : (tid == 69) ? &maps.o
                                                         : &maps.m[blk * 5 + (tid == 65 ? 1 : tid == 66 ? 2 : 4)];
      asm volatile("prefetch.tensormap [%0];" ::"l"(m) : "memory");
    }
    if (wi == 3) {
      __nanosleep(20000);
      __nv_bfloat16* o = out + (size_t)(b * 80 + kvh * 10) * 896 + blk * 448;
#pragma unroll 1
      for (int r = 0; r < 10; r++) {
        *reinterpret_cast<uint4*>(o + r * 896 + lane * 8) = make_uint4(0, 0, 0, 0);
        if (lane < 24) *reinterpret_cast<uint4*>(o + r * 896 + 256 + lane * 8) = make_uint4(0, 0, 0, 0);
      }
      __threadfence();
      __syncwarp();
      if (lane == 0) {
        uint32_t old;
        asm volatile("atom.release.gpu.global.add.u32 %0, [%1], 1;" : "=r"(old) : "l"(g_zero + (blk * 8 + b) * 32) : "memory");
        asm volatile("st.shared.u32 [%0], %1;" ::"r"(sb + OFF_MISC), "r"((old | 7u) + 1u) : "memory");
        mbar_arrive(sb + BAR_T);
      }
    }
    if (tid == 0) {
      const CUtensorMap* mk = &maps.m[blk * 5 + 1];
      const CUtensorMap* mv = &maps.m[blk * 5 + 2];
      const CUtensorMap* mwq = &maps.m[blk * 5 + 3];
      const CUtensorMap* mwo = &maps.m[blk * 5 + 4];
      const int row0 = (b * 8 + kvh) * 1024;
      uint32_t tstart, t1 = 0, t2 = 0;
      asm volatile("mov.u32 %0, %%globaltimer_lo;" : "=r"(tstart));
      uint64_t pol;
      asm volatile("createpolicy.fractional.L2::evict_first.b64 %0, 1.0;" : "=l"(pol));
      const CUtensorMap* mx = &maps.m[blk * 5 + 0];
      uint32_t st = 2, ph = 0;
#pragma unroll 1
      for (int t = 6; t < 28; t++) {
        if (t == 6) tma3d_pf(mwq, 16 * (6 + b), kvh * 8);
        if (t == 10) tma3d_pf(mwq, 16 * (14 + b), kvh * 8);
        if (t == 14 && b < 6) tma3d_pf(mwq, 16 * (22 + b), kvh * 8);
        if (t >= 18 && t < 26 && !(t & 1)) {
          const int q = (t - 18) >> 1;
          if (q == 0) mbar_expect_tx(sb + BAR_FULL, SLOT_B);
          tma3d_ef(sb + OFF_SLOT + q * 8192, &maps.k8[blk], row0, q, sb + BAR_FULL, pol);
        }
        mbar_wait(sb + BAR_WEMPT + 8 * st, ph);
        const int xc = t - 1;
        const bool hx = xc < 7;
        mbar_expect_tx(sb + BAR_WFULL + 8 * st, hx ? WST_B + 10240 : WST_B);
        tma3d(sb + OFF_W + st * WST_B, mwq, 16 * t, kvh * 8, sb + BAR_WFULL + 8 * st);
        if (hx) tma3d(sb + OFF_Q + xc * 10240, mx, b * 80, xc, sb + BAR_WFULL + 8 * st);
        if (++st == 6) st = 0;
        if (st == 2) ph ^= 1;
      }
      mbar_wait(sb + BAR_WEMPT, 1);
      mbar_wait(sb + BAR_WEMPT + 8, 1);
      mbar_expect_tx(sb + BAR_FULL + 8, SLOT_B);
      tma3d_ef(sb + OFF_SLOT + SLOT_B, mk, row0 + 64, 0, sb + BAR_FULL + 8, pol);
      mbar_wait(sb + BAR_WEMPT + 16, 0);
      mbar_wait(sb + BAR_WEMPT + 24, 0);
#pragma unroll 1
      for (int i = 2; i < 32; i++) {
        uint32_t s, use;
        kv_slot(i, s, use);
        const bool isv = !(i & 1);
        const int j = isv ? ((i - 2) >> 1) : ((i + 1) >> 1);
        if (i == 3) {
          mbar_wait(sb + BAR_K0, 0);
          mbar_arrive_n(sb + BAR_EMPTY, 8);
        }
        if (use > 0) mbar_wait(sb + BAR_EMPTY + 8 * s, (use - 1) & 1);
        {
          uint32_t due = PACE_T0 + i * PACE_TAU, now;
          if (i >= 8) due = max(due, t2 + 2 * PACE_MIN);
          do { asm volatile("mov.u32 %0, %%globaltimer_lo;" : "=r"(now)); } while (now - tstart < due);
          t2 = t1;
          t1 = now - tstart;
        }
        if (i == 31) {
          mbar_expect_tx(sb + BAR_VL, SLOT_B / 2);
          tma3d_ef(sb + OFF_SLOT + s * SLOT_B, &maps.v16[blk], row0 + 960, 0, sb + BAR_VL, pol);
          mbar_expect_tx(sb + BAR_FULL + 8 * s, SLOT_B / 2);
          tma3d_ef(sb + OFF_SLOT + s * SLOT_B + SLOT_B / 2, &maps.v16[blk], row0 + 960, 2, sb + BAR_FULL + 8 * s, pol);
          break;
        }
        mbar_expect_tx(sb + BAR_FULL + 8 * s, SLOT_B);
        tma3d_ef(sb + OFF_SLOT + s * SLOT_B, isv ? mv : mk, row0 + 64 * j, 0, sb + BAR_FULL + 8 * s, pol);
      }
#pragma unroll 1
      for (int u = 0; u < 14; u++) {
        uint32_t s, use;
        wo_slot(u, s, use);
        if (use > 0) mbar_wait(sb + BAR_EMPTY + 8 * s, (use - 1) & 1);
        mbar_expect_tx(sb + BAR_FULL + 8 * s, SLOT_B);
        tma3d(sb + OFF_SLOT + s * SLOT_B, mwo, kvh * 512 + 256 * (u & 1), u >> 1, sb + BAR_FULL + 8 * s);
      }
    }
  } else if (wg == 1) {
    asm volatile("setmaxnreg.dec.sync.aligned.u32 104;");
    nb_sync(0, 480);
    ROLE_IDS();
    float m[5], l[5];
#pragma unroll
    for (int r = 0; r < 5; r++) { m[r] = -INFINITY; l[r] = 0.f; }
    SCtx cx;
    {
      const uint32_t li = lane & 7, lm = lane >> 3;
      cx.pa01 = sb + OFF_P + (16 * wi + li + 8 * (lm & 1)) * 128 + (((lm >> 1) ^ li) << 4);
      cx.pa2 = sb + OFF_P + (128 + 8 * wi + li) * 128 + ((lm ^ li) << 4);
      const uint32_t r8 = lane >> 2;
      cx.sa01 = sb + OFF_SC + (40 * (r8 >> 1) + 2 * (2 * wi) + (r8 & 1)) * 4;
      cx.sa2 = sb + OFF_SC + (40 * (r8 >> 1) + 2 * (16 + wi) + (r8 & 1)) * 4;
      cx.wr = (lane & 3) == 0;
    }
    nb_sync(NB_Q, 384);
    {
      float s0[32];
      uint32_t flag = 0;
      mbar_wait(sb + BAR_FULL, 0);
      qk_issue<2>(s0, dlo(sb + OFF_SLOT));
      nb_arrive(NB_GO, 384);
      wg_wait<0>();
      reg_fence<32>(s0);
      if (lane == 0) mbar_arrive(sb + BAR_K0);
      softmax_blk<2>(s0, m, l, flag, cx, [] {});
      fence_async();
      nb_arrive(NB_PFULL, 384);
      cx.pa01 += QCHUNK; cx.pa2 += QCHUNK; cx.sa01 += 640; cx.sa2 += 640;
    }
#pragma unroll 1
    for (int j = 1; j < 16; j++) s_tile(j, m, l, cx, wi, lane);
#pragma unroll
    for (int r = 0; r < 5; r++) {
      float lr = l[r];
      lr += __shfl_xor_sync(0xffffffffu, lr, 1);
      lr += __shfl_xor_sync(0xffffffffu, lr, 2);
      float inv;
      asm("rcp.approx.ftz.f32 %0, %1;" : "=f"(inv) : "f"(lr));
      if (cx.wr) sts32((r < 4 ? cx.sa01 + (r >> 1) * 64 + (r & 1) * 8 : cx.sa2) + (OFF_LINV - OFF_SC), inv);
    }
    nb_arrive(NB_O2, 384);
    uint32_t tid2, bid2;
    asm volatile("mov.u32 %0, %%tid.x;" : "=r"(tid2));
    asm volatile("mov.u32 %0, %%ctaid.x;" : "=r"(bid2));
    if (tid2 < 160) {
      if (tid2 == 128) {
        uint32_t target, z, it = 0;
        mbar_wait(sb + BAR_T, 0);
        asm volatile("ld.shared.u32 %0, [%1];" : "=r"(target) : "r"(sb + OFF_MISC) : "memory");
        do {
          asm volatile("ld.acquire.gpu.global.u32 %0, [%1];" : "=r"(z) : "l"(g_zero + ((bid2 >> 6) * 8 + (bid2 & 7)) * 32) : "memory");
          if (++it > (1u << 22)) __trap();
        } while ((int)(z - target) < 0);
        asm volatile("fence.proxy.async;" ::: "memory");
      }
#pragma unroll 1
      for (int p = 0; p < 7; p++) {
        nb_sync(NB_SF + (p & 1), 160);
        if (tid2 == 128) {
#pragma unroll
          for (int k = 4; k >= 0; k--) {
            asm volatile("cp.reduce.async.bulk.tensor.3d.global.shared::cta.add.tile.bulk_group [%0, {%1, %2, %3}], [%4];"
                         ::"l"(&maps.o), "r"(0), "r"((bid2 & 7) * 80 + 16 * k), "r"((bid2 >> 6) * 7 + p),
                         "r"(sb + OFF_ST + (k == 4 ? 16384 : (p & 1) * 8192 + k * 2048)) : "memory");
            if (k == 4 || k == 0) asm volatile("cp.async.bulk.commit_group;" ::: "memory");
          }
          asm volatile("cp.async.bulk.wait_group.read 1;" ::: "memory");
        }
        __syncwarp();
        if (p < 6) nb_arrive(nb_se((p + 1) & 1), 160);
        if (tid2 == 128) asm volatile("cp.async.bulk.wait_group.read 0;" ::: "memory");
        __syncwarp();
        if (p < 5) nb_arrive(NB_GO + (p & 1), 160);
      }
    }
  } else {
    asm volatile("setmaxnreg.inc.sync.aligned.u32 192;");
    ROLE_IDS();
    const int w = __shfl_sync(0xffffffffu, (tid >> 7) & 1, 0);
    const uint32_t li = lane & 7, lm = lane >> 3;
    {
      float acc[160];
#pragma unroll
      for (int i = 0; i < 160; i++) acc[i] = 0.f;
      reg_fence<160>(acc);
      nb_sync(0, 480);
      uint32_t st = 2, ph = 0, pst = 0, ok = 0;
#pragma unroll 1
      for (int t = 0; t < 28; t++) {
        if (!ok) mbar_wait(sb + BAR_WFULL + 8 * st, ph);
        const uint32_t nst = (st == 5) ? 0 : st + 1, nph = (nst == 2) ? ph ^ 1 : ph;
        ok = mbar_test(sb + BAR_WFULL + 8 * nst, nph);
        const uint32_t da = dlo(sb + OFF_W) + st * (WST_B >> 4) + w * (8192 >> 4);
        const uint32_t db = dlo(sb + OFF_Q) + (((t >> 2) * 10240 + (t & 3) * 32) >> 4);
        wg_fence();
        static_for<0, 4>([&](auto C) { constexpr int cc = decltype(C)::value; wgmma_n80_mk1<cc * 2048, 0>(acc + 40 * cc, da, db); });
        wg_commit();
        wg_wait<1>();
        if (t > 0 && lane == 0) mbar_arrive(sb + BAR_WEMPT + 8 * pst);
        pst = st;
        st = nst;
        ph = nph;
      }
      wg_wait<0>();
      reg_fence<160>(acc);
      const uint32_t qa = sb + OFF_Q + (80 * w + 8 * (lm >> 1) + li) * 128 + (((2 * wi + (lm & 1)) ^ li) << 4);
#pragma unroll
      for (int cc = 0; cc < 4; cc++) {
        if (cc == 2) nb_sync(NB_O, 256);
#pragma unroll
        for (int jj = 0; jj < 5; jj++) {
          const float* q = acc + 40 * cc + 8 * jj;
          stsm4t(qa + cc * QCHUNK + jj * 2048, pack_bf16(q[0], q[1]), pack_bf16(q[2], q[3]), pack_bf16(q[4], q[5]),
                 pack_bf16(q[6], q[7]));
        }
      }
      fence_async();
      nb_arrive(NB_Q, 384);
    }
    {
      float s0[32], mc[2] = {-INFINITY, -INFINITY}, l[2] = {0.f, 0.f};
      uint32_t flag = 0;
      SCtx cx;
      cx.pa01 = sb + OFF_P + w * 8192 + (16 * wi + li + 8 * (lm & 1)) * 128 + (((lm >> 1) ^ li) << 4);
      cx.sa01 = 0; cx.pa2 = 0; cx.sa2 = 0;
      cx.wr = false;
      mbar_wait(sb + BAR_FULL, 0);
      nb_sync(NB_GO, 384);
      qk_issue<0>(s0, dlo(sb + OFF_SLOT), w * (8192 >> 4));
      wg_wait<0>();
      reg_fence<32>(s0);
      if (lane == 0) mbar_arrive(sb + BAR_K0);
      softmax_blk<0>(s0, mc, l, flag, cx, [] {});
      asm volatile("st.shared.v4.f32 [%0], {%1, %2, %3, %4};" ::"r"(sb + OFF_ML + w * 2048 + (tid & 127) * 16), "f"(mc[0]),
                   "f"(mc[1]), "f"(l[0]), "f"(l[1]) : "memory");
      fence_async();
      nb_arrive(NB_S, 384);
    }
    {
    float acc[160];
#pragma unroll
    for (int i = 0; i < 160; i++) acc[i] = 0.f;
    reg_fence<160>(acc);
#pragma unroll 1
    for (int j = 0; j < 16; j++) {
      const uint32_t pb = j & 1;
      nb_sync(NB_PFULL + pb, 384);
      if (j > 0) {
        const float4 f = lds128(sb + OFF_FLAG + pb * 16);
        if ((__float_as_uint(f.x) | __float_as_uint(f.y) | __float_as_uint(f.z) | __float_as_uint(f.w)) != 0) {
          const uint32_t sc = sb + OFF_SC + pb * 640 + (lane & 3) * 160;
#pragma unroll
          for (int g = 0; g < 10; g++) {
            const float4 a = lds128(sc + g * 16);
#pragma unroll
            for (int mb = 0; mb < 2; mb++) {
              float* q = acc + 80 * mb + 8 * g;
              q[0] *= a.x; q[1] *= a.y; q[2] *= a.x; q[3] *= a.y;
              q[4] *= a.z; q[5] *= a.w; q[6] *= a.z; q[7] *= a.w;
            }
          }
        }
      }
      uint32_t slot, use;
      kv_slot(j == 15 ? 31 : 2 * j + 2, slot, use);
      reg_fence<160>(acc);
      if (j < 15) nb_sync(NB_GO, 384);
      else if (w == 1) nb_sync(NB_O, 256);
      if (j == 15 && w == 0) mbar_wait(sb + BAR_VL, 0);
      else mbar_wait(sb + BAR_FULL + 8 * slot, use & 1);
      const uint32_t da = dlo(sb + OFF_SLOT) + slot * (SLOT_B >> 4) + w * (16384 >> 4);
      const uint32_t db = dlo(sb + OFF_P) + pb * (QCHUNK >> 4);
      wg_fence();
      static_for<0, 4>([&](auto K) {
        constexpr int ks = decltype(K)::value;
        wgmma_n160_mk1<ks * 2048, ks * 32>(acc, da, db);
        wgmma_n160_mk1<8192 + ks * 2048, ks * 32>(acc + 80, da, db);
      });
      wg_commit();
      if (j == 15 && w == 0) nb_arrive(NB_O, 256);
      wg_wait<0>();
      reg_fence<160>(acc);
      if (lane == 0) mbar_arrive(sb + BAR_EMPTY + 8 * slot);
      if (j < 14) nb_arrive(NB_PEMPTY + pb, 384);
    }
    {
      const uint32_t oa = sb + OFF_Q + 2 * w * QCHUNK + (8 * (lm >> 1) + li) * 128 + (((2 * wi + (lm & 1)) ^ li) << 4);
#pragma unroll
      for (int mb = 0; mb < 2; mb++)
#pragma unroll
        for (int jj = 0; jj < 10; jj++) {
          const float* q = acc + 80 * mb + 8 * jj;
          stsm4t(oa + mb * QCHUNK + jj * 2048, pack_bf16(q[0], q[1]), pack_bf16(q[2], q[3]), pack_bf16(q[4], q[5]),
                 pack_bf16(q[6], q[7]));
        }
      fence_async();
    }
    }
    nb_sync(NB_O2, 384);
    constexpr uint32_t dob = dlo(sb + OFF_Q);
    const uint32_t sta = sb + OFF_ST + (8 * (lm >> 1) + li) * 128 + (((2 * wi + (lm & 1)) ^ li) << 4);
    float linv[40];
#pragma unroll
    for (int g = 0; g < 10; g++) {
      const float4 f = lds128(sb + OFF_LINV + (lane & 3) * 160 + g * 16);
      linv[4 * g] = f.x; linv[4 * g + 1] = f.y; linv[4 * g + 2] = f.z; linv[4 * g + 3] = f.w;
    }
#pragma unroll 1
    for (int p = w; p < 7; p += 2) {
      float acc[40], acc1[40];
      uint32_t slot0, use0, slot1, use1;
      wo_slot(2 * p, slot0, use0);
      wo_slot(2 * p + 1, slot1, use1);
      mbar_wait(sb + BAR_FULL + 8 * slot0, use0 & 1);
      if (p > 0) nb_sync(NB_ORD + w, 256);
      uint32_t da = dlo(sb + OFF_SLOT) + slot0 * (SLOT_B >> 4);
      wg_fence();
      wgmma_n80_mk_z<0, 0>(acc, da, dob);
      static_for<1, 9>([&](auto K) {
        constexpr int ks = decltype(K)::value;
        wgmma_n80_mk1<ks * 2048, (ks >> 2) * QCHUNK + (ks & 3) * 32>(acc, da, dob);
      });
      const uint32_t ok1 = mbar_test(sb + BAR_FULL + 8 * slot1, use1 & 1);
      static_for<9, 16>([&](auto K) {
        constexpr int ks = decltype(K)::value;
        wgmma_n80_mk1<ks * 2048, (ks >> 2) * QCHUNK + (ks & 3) * 32>(acc, da, dob);
      });
      wg_commit();
      if (!ok1) mbar_wait(sb + BAR_FULL + 8 * slot1, use1 & 1);
      da = dlo(sb + OFF_SLOT) + slot1 * (SLOT_B >> 4);
      wg_fence();
      wgmma_n80_mk_z<0, 10240>(acc1, da, dob);
      static_for<1, 6>([&](auto K) {
        constexpr int ks = decltype(K)::value;
        wgmma_n80_mk1<ks * 2048, 10240 + (ks >> 2) * QCHUNK + (ks & 3) * 32>(acc1, da, dob);
      });
      wg_commit();
      wg_wait<1>();
      if (lane == 0) mbar_arrive_n(sb + BAR_EMPTY + 8 * slot0, 2);
      wg_fence();
      static_for<6, 16>([&](auto K) {
        constexpr int ks = decltype(K)::value;
        wgmma_n80_mk1<ks * 2048, 10240 + (ks >> 2) * QCHUNK + (ks & 3) * 32>(acc1, da, dob);
      });
      wg_commit();
      if (p < 6) nb_arrive(NB_ORD + (w ^ 1), 256);
      wg_wait<0>();
      reg_fence<40>(acc);
      reg_fence<40>(acc1);
      if (lane == 0) mbar_arrive_n(sb + BAR_EMPTY + 8 * slot1, 2);
#pragma unroll
      for (int i = 0; i < 40; i++)
        acc[i] = fmaf(acc[i], linv[2 * (i >> 2) + (i & 1)], acc1[i] * linv[20 + 2 * (i >> 2) + (i & 1)]);
      uint32_t pk[20];
#pragma unroll
      for (int i = 0; i < 20; i++) pk[i] = pack_bf16(acc[2 * i], acc[2 * i + 1]);
      if (p > 1) nb_sync(NB_GO + w, 160);
#pragma unroll
      for (int k = 0; k < 4; k++) stsm4t(sta + w * 8192 + k * 2048, pk[4 * k], pk[4 * k + 1], pk[4 * k + 2], pk[4 * k + 3]);
      if (p > 0) nb_sync(nb_se(w), 160);
      stsm4t(sta + 16384, pk[16], pk[17], pk[18], pk[19]);
      fence_async();
      nb_arrive(NB_SF + w, 160);
    }
  }
}

typedef CUresult (*EncodeFn)(CUtensorMap*, CUtensorMapDataType, cuuint32_t, void*, const cuuint64_t*, const cuuint64_t*,
                             const cuuint32_t*, const cuuint32_t*, CUtensorMapInterleave, CUtensorMapSwizzle,
                             CUtensorMapL2promotion, CUtensorMapFloatOOBfill);

void encode3d(EncodeFn enc, CUtensorMap* m, void* p, uint64_t rows, uint64_t cols, uint32_t box_rows,
              uint32_t box_blocks) {
  cuuint64_t dims[3] = {64, rows, cols / 64};
  cuuint64_t strides[2] = {cols * 2, 128};
  cuuint32_t box[3] = {64, box_rows, box_blocks};
  cuuint32_t es[3] = {1, 1, 1};
  enc(m, CU_TENSOR_MAP_DATA_TYPE_BFLOAT16, 3, p, dims, strides, box, es, CU_TENSOR_MAP_INTERLEAVE_NONE,
      CU_TENSOR_MAP_SWIZZLE_128B,
      cols == 256 ? CU_TENSOR_MAP_L2_PROMOTION_L2_256B : CU_TENSOR_MAP_L2_PROMOTION_L2_128B,
      CU_TENSOR_MAP_FLOAT_OOB_FILL_NONE);
}

}

extern "C" void kernel_launch(void* const* d_in, const int* in_sizes, int n_in, void* d_out, int out_size) {
  static EncodeFn enc = nullptr;
  if (!enc) {
    void* fn = nullptr;
    cudaDriverEntryPointQueryResult qr;
    cudaGetDriverEntryPoint("cuTensorMapEncodeTiled", &fn, cudaEnableDefault, &qr);
    enc = (EncodeFn)fn;
    cudaFuncSetAttribute(fused_gqa_kernel, cudaFuncAttributeMaxDynamicSharedMemorySize, SMEM_BYTES);
  }
  Maps maps;
  for (int blk = 0; blk < 2; blk++) {
    encode3d(enc, &maps.m[blk * 5 + 0], d_in[blk * 5 + 0], 640, 448, 80, 1);
    encode3d(enc, &maps.m[blk * 5 + 1], d_in[blk * 5 + 1], 65536, 256, 64, 4);
    encode3d(enc, &maps.m[blk * 5 + 2], d_in[blk * 5 + 2], 65536, 256, 64, 4);
    encode3d(enc, &maps.m[blk * 5 + 3], d_in[blk * 5 + 3], 448, 4096, 16, 8);
    encode3d(enc, &maps.m[blk * 5 + 4], d_in[blk * 5 + 4], 4096, 448, 256, 1);
    encode3d(enc, &maps.k8[blk], d_in[blk * 5 + 1], 65536, 256, 64, 1);
    encode3d(enc, &maps.v16[blk], d_in[blk * 5 + 2], 65536, 256, 64, 2);
  }
  encode3d(enc, &maps.o, d_out, 640, 896, 16, 1);
  fused_gqa_kernel<<<NCTA, NTHREADS, SMEM_BYTES>>>(maps, (__nv_bfloat16*)d_out);
}
```

```cpp
#include <cuda_runtime.h>
#include <cuda_bf16.h>
#include <cuda.h>
#include <stdint.h>

namespace {

constexpr int NCTA = 128;
constexpr int NTHREADS = 512;

constexpr uint32_t SB = 0x400;
constexpr uint32_t OFF_Q     = 0;
constexpr uint32_t QCHUNK    = 20480;
constexpr uint32_t OFF_SLOT  = 81920;
constexpr uint32_t SLOT_B    = 32768;
constexpr uint32_t OFF_P     = OFF_SLOT + 3 * SLOT_B;
constexpr uint32_t OFF_W     = OFF_SLOT + SLOT_B;
constexpr uint32_t WST_B     = 16384;
constexpr uint32_t OFF_SC    = OFF_P + 2 * QCHUNK;
constexpr uint32_t OFF_FLAG  = OFF_SC + 1280;
constexpr uint32_t OFF_LINV  = OFF_FLAG + 32;
constexpr uint32_t OFF_ST    = OFF_P + SLOT_B;
constexpr uint32_t OFF_ML    = OFF_ST + 10240;
constexpr uint32_t OFF_BAR   = OFF_ST + 18432;
constexpr uint32_t BAR_FULL  = OFF_BAR;
constexpr uint32_t BAR_EMPTY = BAR_FULL + 32;
constexpr uint32_t BAR_WFULL = BAR_EMPTY + 32;
constexpr uint32_t BAR_WEMPT = BAR_WFULL + 48;
constexpr uint32_t BAR_T     = BAR_WEMPT + 48;
constexpr uint32_t BAR_VL    = BAR_T + 8;
constexpr uint32_t BAR_K0    = BAR_VL + 8;
constexpr uint32_t OFF_MISC  = BAR_K0 + 8;
constexpr uint32_t SMEM_BYTES = OFF_MISC + 16;

#define PACE_TAU 1320
#define PACE_T0 3200
#define PACE_MIN 1250

struct Maps {
  CUtensorMap m[10];
  CUtensorMap k8[2];
  CUtensorMap v16[2];
  CUtensorMap o;
};

__device__ unsigned int g_zero[16 * 32];

__device__ __forceinline__ void mbar_init(uint32_t bar, uint32_t cnt) {
  asm volatile("mbarrier.init.shared::cta.b64 [%0], %1;" ::"r"(bar), "r"(cnt) : "memory");
}
__device__ __forceinline__ void mbar_expect_tx(uint32_t bar, uint32_t bytes) {
  asm volatile("mbarrier.arrive.expect_tx.shared::cta.b64 _, [%0], %1;" ::"r"(bar), "r"(bytes) : "memory");
}
__device__ __forceinline__ void mbar_arrive(uint32_t bar) {
  asm volatile("mbarrier.arrive.shared::cta.b64 _, [%0];" ::"r"(bar) : "memory");
}
__device__ __forceinline__ void mbar_arrive_n(uint32_t bar, uint32_t n) {
  asm volatile("mbarrier.arrive.shared::cta.b64 _, [%0], %1;" ::"r"(bar), "r"(n) : "memory");
}
__device__ __forceinline__ void mbar_wait(uint32_t bar, uint32_t parity) {
  asm volatile(
      "{\n.reg .pred p;\n.reg .u32 c;\nmov.u32 c, 0;\n"
      "W_LOOP:\n"
      "mbarrier.try_wait.parity.shared::cta.b64 p, [%0], %1;\n"
      "@p bra W_DONE;\n"
      "add.u32 c, c, 1;\n"
      "setp.lt.u32 p, c, 0x80000;\n"
      "@p bra W_LOOP;\n"
      "trap;\n"
      "W_DONE:\n}\n" ::"r"(bar), "r"(parity) : "memory");
}
__device__ __forceinline__ uint32_t mbar_test(uint32_t bar, uint32_t parity) {
  uint32_t ok;
  asm volatile("{\n.reg .pred p;\nmbarrier.test_wait.parity.shared::cta.b64 p, [%1], %2;\nselp.u32 %0, 1, 0, p;\n}\n"
               : "=r"(ok) : "r"(bar), "r"(parity) : "memory");
  return ok;
}
__device__ __forceinline__ void nb_sync(uint32_t id, uint32_t n) { asm volatile("bar.sync %0, %1;" ::"r"(id), "r"(n) : "memory"); }
__device__ __forceinline__ void nb_arrive(uint32_t id, uint32_t n) { asm volatile("bar.arrive %0, %1;" ::"r"(id), "r"(n) : "memory"); }
constexpr uint32_t NB_O = 1, NB_PFULL = 2, NB_PEMPTY = 4, NB_GO = 6, NB_Q = 8, NB_ORD = 10, NB_O2 = 12, NB_S = 13, NB_SF = 14;
__device__ __forceinline__ uint32_t nb_se(uint32_t w) { return w ? NB_S : NB_Q; }
__device__ __forceinline__ void tma3d(uint32_t dst, const CUtensorMap* m, int c1, int c2, uint32_t bar) {
  asm volatile(
      "cp.async.bulk.tensor.3d.shared::cluster.global.mbarrier::complete_tx::bytes [%0], [%1, {%2, %3, %4}], [%5];"
      ::"r"(dst), "l"(m), "r"(0), "r"(c1), "r"(c2), "r"(bar) : "memory");
}
__device__ __forceinline__ void tma3d_ef(uint32_t dst, const CUtensorMap* m, int c1, int c2, uint32_t bar, uint64_t pol) {
  asm volatile(
      "cp.async.bulk.tensor.3d.shared::cluster.global.mbarrier::complete_tx::bytes.L2::cache_hint [%0], [%1, {%2, %3, %4}], [%5], %6;"
      ::"r"(dst), "l"(m), "r"(0), "r"(c1), "r"(c2), "r"(bar), "l"(pol) : "memory");
}
__device__ __forceinline__ void tma3d_pf(const CUtensorMap* m, int c1, int c2) {
  asm volatile("cp.async.bulk.prefetch.tensor.3d.L2.global [%0, {%1, %2, %3}];" ::"l"(m), "r"(0), "r"(c1), "r"(c2)
               : "memory");
}
__device__ __forceinline__ void wg_fence() { asm volatile("wgmma.fence.sync.aligned;" ::: "memory"); }
__device__ __forceinline__ void wg_commit() { asm volatile("wgmma.commit_group.sync.aligned;" ::: "memory"); }
template <int N>
__device__ __forceinline__ void wg_wait() { asm volatile("wgmma.wait_group.sync.aligned %0;" ::"n"(N) : "memory"); }
__device__ __forceinline__ void fence_async() { asm volatile("fence.proxy.async.shared::cta;" ::: "memory"); }
template <int N>
__device__ __forceinline__ void reg_fence(float* d) {
#pragma unroll
  for (int i = 0; i < N; i++) asm volatile("" : "+f"(d[i])::"memory");
}
__device__ __forceinline__ constexpr uint32_t dlo(uint32_t saddr) { return ((saddr & 0x3FFFFu) >> 4) | (1u << 16); }
template <int V>
struct IC { static constexpr int value = V; };
template <int I, int N, class F>
__device__ __forceinline__ void static_for(F&& f) {
  if constexpr (I < N) {
    f(IC<I>{});
    static_for<I + 1, N>(f);
  }
}
__device__ __forceinline__ uint32_t pack_bf16(float lo, float hi) {
  uint32_t r;
  asm("cvt.rn.bf16x2.f32 %0, %1, %2;" : "=r"(r) : "f"(hi), "f"(lo));
  return r;
}
template <uint32_t XR, uint32_t OFF>
__device__ __forceinline__ void stsm4_o(uint32_t a, uint32_t r0, uint32_t r1, uint32_t r2, uint32_t r3) {
  asm volatile("{\n.reg .b32 t;\nxor.b32 t, %0, %6;\nstmatrix.sync.aligned.m8n8.x4.shared.b16 [t + %5], {%1, %2, %3, %4};\n}\n"
               ::"r"(a), "r"(r0), "r"(r1), "r"(r2), "r"(r3), "n"(OFF), "n"(XR) : "memory");
}
__device__ __forceinline__ void stsm4t(uint32_t a, uint32_t r0, uint32_t r1, uint32_t r2, uint32_t r3) {
  asm volatile("stmatrix.sync.aligned.m8n8.x4.trans.shared.b16 [%0], {%1, %2, %3, %4};" ::"r"(a), "r"(r0), "r"(r1),
               "r"(r2), "r"(r3) : "memory");
}
__device__ __forceinline__ float ex2(float x) {
  float y;
  asm("ex2.approx.ftz.f32 %0, %1;" : "=f"(y) : "f"(x));
  return y;
}
__device__ __forceinline__ float4 lds128(uint32_t a) {
  float4 v;
  asm volatile("ld.shared.v4.f32 {%0, %1, %2, %3}, [%4];" : "=f"(v.x), "=f"(v.y), "=f"(v.z), "=f"(v.w) : "r"(a) : "memory");
  return v;
}
__device__ __forceinline__ void sts32(uint32_t a, float v) {
  asm volatile("st.shared.f32 [%0], %1;" ::"r"(a), "f"(v) : "memory");
}
template <uint32_t OA, uint32_t OB, uint32_t HIA = 0x40000040u>
__device__ __forceinline__ void wgmma_n64_kk_z(float* d, uint32_t a, uint32_t b) {
  asm volatile(
      "{\n.reg .b32 ta, tb;\n.reg .b64 da, db;\nadd.u32 ta, %32, %34;\nadd.u32 tb, %33, %35;\nmov.b64 da, {ta, %36};\nmov.b64 db, {tb, 0x40000040};\n"
      "wgmma.mma_async.sync.aligned.m64n64k16.f32.bf16.bf16 {"
      "%0, %1, %2, %3, %4, %5, %6, %7, %8, %9, %10, %11, %12, %13, %14, %15,"
      "%16, %17, %18, %19, %20, %21, %22, %23, %24, %25, %26, %27, %28, %29, %30, %31}, da, db, 0, 1, 1, 0, 0;\n}\n"
      : "=f"(d[0]), "=f"(d[1]), "=f"(d[2]), "=f"(d[3]), "=f"(d[4]), "=f"(d[5]), "=f"(d[6]), "=f"(d[7]),
        "=f"(d[8]), "=f"(d[9]), "=f"(d[10]), "=f"(d[11]), "=f"(d[12]), "=f"(d[13]), "=f"(d[14]), "=f"(d[15]),
        "=f"(d[16]), "=f"(d[17]), "=f"(d[18]), "=f"(d[19]), "=f"(d[20]), "=f"(d[21]), "=f"(d[22]), "=f"(d[23]),
        "=f"(d[24]), "=f"(d[25]), "=f"(d[26]), "=f"(d[27]), "=f"(d[28]), "=f"(d[29]), "=f"(d[30]), "=f"(d[31])
      : "r"(a), "r"(b), "n"(OA >> 4), "n"(OB >> 4), "n"(HIA));
}

template <uint32_t OA, uint32_t OB, uint32_t HIA = 0x40000040u>
__device__ __forceinline__ void wgmma_n64_kk(float* d, uint32_t a, uint32_t b) {
  asm volatile(
      "{\n.reg .b32 ta, tb;\n.reg .b64 da, db;\nadd.u32 ta, %32, %34;\nadd.u32 tb, %33, %35;\nmov.b64 da, {ta, %36};\nmov.b64 db, {tb, 0x40000040};\n"
      "wgmma.mma_async.sync.aligned.m64n64k16.f32.bf16.bf16 {"
      "%0, %1, %2, %3, %4, %5, %6, %7, %8, %9, %10, %11, %12, %13, %14, %15,"
      "%16, %17, %18, %19, %20, %21, %22, %23, %24, %25, %26, %27, %28, %29, %30, %31}, da, db, 1, 1, 1, 0, 0;\n}\n"
      : "+f"(d[0]), "+f"(d[1]), "+f"(d[2]), "+f"(d[3]), "+f"(d[4]), "+f"(d[5]), "+f"(d[6]), "+f"(d[7]),
        "+f"(d[8]), "+f"(d[9]), "+f"(d[10]), "+f"(d[11]), "+f"(d[12]), "+f"(d[13]), "+f"(d[14]), "+f"(d[15]),
        "+f"(d[16]), "+f"(d[17]), "+f"(d[18]), "+f"(d[19]), "+f"(d[20]), "+f"(d[21]), "+f"(d[22]), "+f"(d[23]),
        "+f"(d[24]), "+f"(d[25]), "+f"(d[26]), "+f"(d[27]), "+f"(d[28]), "+f"(d[29]), "+f"(d[30]), "+f"(d[31])
      : "r"(a), "r"(b), "n"(OA >> 4), "n"(OB >> 4), "n"(HIA));
}

template <uint32_t OA, uint32_t OB, uint32_t HIA = 0x40000040u>
__device__ __forceinline__ void wgmma_n80_mk_z(float* d, uint32_t a, uint32_t b) {
  asm volatile(
      "{\n.reg .b32 ta, tb;\n.reg .b64 da, db;\nadd.u32 ta, %40, %42;\nadd.u32 tb, %41, %43;\nmov.b64 da, {ta, %44};\nmov.b64 db, {tb, 0x40000040};\n"
      "wgmma.mma_async.sync.aligned.m64n80k16.f32.bf16.bf16 {"
      "%0, %1, %2, %3, %4, %5, %6, %7, %8, %9, %10, %11, %12, %13, %14, %15,"
      "%16, %17, %18, %19, %20, %21, %22, %23, %24, %25, %26, %27, %28, %29, %30, %31,"
      "%32, %33, %34, %35, %36, %37, %38, %39}, da, db, 0, 1, 1, 1, 0;\n}\n"
      : "=f"(d[0]), "=f"(d[1]), "=f"(d[2]), "=f"(d[3]), "=f"(d[4]), "=f"(d[5]), "=f"(d[6]), "=f"(d[7]),
        "=f"(d[8]), "=f"(d[9]), "=f"(d[10]), "=f"(d[11]), "=f"(d[12]), "=f"(d[13]), "=f"(d[14]), "=f"(d[15]),
        "=f"(d[16]), "=f"(d[17]), "=f"(d[18]), "=f"(d[19]), "=f"(d[20]), "=f"(d[21]), "=f"(d[22]), "=f"(d[23]),
        "=f"(d[24]), "=f"(d[25]), "=f"(d[26]), "=f"(d[27]), "=f"(d[28]), "=f"(d[29]), "=f"(d[30]), "=f"(d[31]),
        "=f"(d[32]), "=f"(d[33]), "=f"(d[34]), "=f"(d[35]), "=f"(d[36]), "=f"(d[37]), "=f"(d[38]), "=f"(d[39])
      : "r"(a), "r"(b), "n"(OA >> 4), "n"(OB >> 4), "n"(HIA));
}

template <uint32_t OA, uint32_t OB, uint32_t HIA = 0x40000040u>
__device__ __forceinline__ void wgmma_n80_mk1(float* d, uint32_t a, uint32_t b) {
  asm volatile(
      "{\n.reg .b32 ta, tb;\n.reg .b64 da, db;\nadd.u32 ta, %40, %42;\nadd.u32 tb, %41, %43;\nmov.b64 da, {ta, %44};\nmov.b64 db, {tb, 0x40000040};\n"
      "wgmma.mma_async.sync.aligned.m64n80k16.f32.bf16.bf16 {"
      "%0, %1, %2, %3, %4, %5, %6, %7, %8, %9, %10, %11, %12, %13, %14, %15,"
      "%16, %17, %18, %19, %20, %21, %22, %23, %24, %25, %26, %27, %28, %29, %30, %31,"
      "%32, %33, %34, %35, %36, %37, %38, %39}, da, db, 1, 1, 1, 1, 0;\n}\n"
      : "+f"(d[0]), "+f"(d[1]), "+f"(d[2]), "+f"(d[3]), "+f"(d[4]), "+f"(d[5]), "+f"(d[6]), "+f"(d[7]),
        "+f"(d[8]), "+f"(d[9]), "+f"(d[10]), "+f"(d[11]), "+f"(d[12]), "+f"(d[13]), "+f"(d[14]), "+f"(d[15]),
        "+f"(d[16]), "+f"(d[17]), "+f"(d[18]), "+f"(d[19]), "+f"(d[20]), "+f"(d[21]), "+f"(d[22]), "+f"(d[23]),
        "+f"(d[24]), "+f"(d[25]), "+f"(d[26]), "+f"(d[27]), "+f"(d[28]), "+f"(d[29]), "+f"(d[30]), "+f"(d[31]),
        "+f"(d[32]), "+f"(d[33]), "+f"(d[34]), "+f"(d[35]), "+f"(d[36]), "+f"(d[37]), "+f"(d[38]), "+f"(d[39])
      : "r"(a), "r"(b), "n"(OA >> 4), "n"(OB >> 4), "n"(HIA));
}

template <uint32_t OA, uint32_t OB, uint32_t HIA = 0x40000040u>
__device__ __forceinline__ void wgmma_n160_mk1(float* d, uint32_t a, uint32_t b) {
  asm volatile(
      "{\n.reg .b32 ta, tb;\n.reg .b64 da, db;\nadd.u32 ta, %80, %82;\nadd.u32 tb, %81, %83;\nmov.b64 da, {ta, %84};\nmov.b64 db, {tb, 0x40000040};\n"
      "wgmma.mma_async.sync.aligned.m64n160k16.f32.bf16.bf16 {"
      "%0, %1, %2, %3, %4, %5, %6, %7, %8, %9, %10, %11, %12, %13, %14, %15,"
      "%16, %17, %18, %19, %20, %21, %22, %23, %24, %25, %26, %27, %28, %29, %30, %31,"
      "%32, %33, %34, %35, %36, %37, %38, %39, %40, %41, %42, %43, %44, %45, %46, %47,"
      "%48, %49, %50, %51, %52, %53, %54, %55, %56, %57, %58, %59, %60, %61, %62, %63,"
      "%64, %65, %66, %67, %68, %69, %70, %71, %72, %73, %74, %75, %76, %77, %78, %79}, da, db, 1, 1, 1, 1, 0;\n}\n"
      : "+f"(d[0]), "+f"(d[1]), "+f"(d[2]), "+f"(d[3]), "+f"(d[4]), "+f"(d[5]), "+f"(d[6]), "+f"(d[7]),
        "+f"(d[8]), "+f"(d[9]), "+f"(d[10]), "+f"(d[11]), "+f"(d[12]), "+f"(d[13]), "+f"(d[14]), "+f"(d[15]),
        "+f"(d[16]), "+f"(d[17]), "+f"(d[18]), "+f"(d[19]), "+f"(d[20]), "+f"(d[21]), "+f"(d[22]), "+f"(d[23]),
        "+f"(d[24]), "+f"(d[25]), "+f"(d[26]), "+f"(d[27]), "+f"(d[28]), "+f"(d[29]), "+f"(d[30]), "+f"(d[31]),
        "+f"(d[32]), "+f"(d[33]), "+f"(d[34]), "+f"(d[35]), "+f"(d[36]), "+f"(d[37]), "+f"(d[38]), "+f"(d[39]),
        "+f"(d[40]), "+f"(d[41]), "+f"(d[42]), "+f"(d[43]), "+f"(d[44]), "+f"(d[45]), "+f"(d[46]), "+f"(d[47]),
        "+f"(d[48]), "+f"(d[49]), "+f"(d[50]), "+f"(d[51]), "+f"(d[52]), "+f"(d[53]), "+f"(d[54]), "+f"(d[55]),
        "+f"(d[56]), "+f"(d[57]), "+f"(d[58]), "+f"(d[59]), "+f"(d[60]), "+f"(d[61]), "+f"(d[62]), "+f"(d[63]),
        "+f"(d[64]), "+f"(d[65]), "+f"(d[66]), "+f"(d[67]), "+f"(d[68]), "+f"(d[69]), "+f"(d[70]), "+f"(d[71]),
        "+f"(d[72]), "+f"(d[73]), "+f"(d[74]), "+f"(d[75]), "+f"(d[76]), "+f"(d[77]), "+f"(d[78]), "+f"(d[79])
      : "r"(a), "r"(b), "n"(OA >> 4), "n"(OB >> 4), "n"(HIA));
}

__device__ __forceinline__ void kv_slot(int i, uint32_t& slot, uint32_t& use) {
  use = (uint32_t)i / 3u;
  slot = (uint32_t)i - use * 3u;
}
__device__ __forceinline__ void wo_slot(int u, uint32_t& slot, uint32_t& use) {
  uint32_t r = u & 3, q = u >> 2;
  slot = (r == 0) ? 2u : (r == 3) ? 3u : (r - 1u);
  use = q + ((r == 0) ? 10u : (r == 3) ? 0u : 11u);
}

struct SCtx {
  uint32_t pa01, pa2, sa01, sa2;
  bool wr;
};

template <int BLK>
__device__ __forceinline__ void qk_issue(float* s, uint32_t dk, uint32_t qoff = 0) {
  const uint32_t dq = dlo(SB + OFF_Q + BLK * 8192) + qoff;
  constexpr uint32_t HI = (BLK == 2) ? 0x40000020u : 0x40000040u;
  wg_fence();
  constexpr uint32_t T = BLK << 20;
  wgmma_n64_kk_z<0, T, HI>(s, dq, dk);
  static_for<1, 16>([&](auto I) {
    constexpr int ks = decltype(I)::value;
    wgmma_n64_kk<(ks >> 2) * QCHUNK + (ks & 3) * 32, T + (ks >> 2) * 8192 + (ks & 3) * 32, HI>(s, dq, dk);
  });
  wg_commit();
}

template <int BLK, class F>
__device__ __forceinline__ void softmax_blk(float* s, float* mc, float* l, uint32_t& flag, const SCtx& cx, F&& mid) {
  constexpr float c = 0.0625f * 1.4426950408889634f;
  constexpr int NR = (BLK == 2) ? 1 : 2;
  float mx[NR], alpha[NR];
  bool need = false;
#pragma unroll
  for (int r = 0; r < NR; r++) {
    float v0 = fmaxf(s[2 * r], s[2 * r + 1]), v1 = fmaxf(s[2 * r + 4], s[2 * r + 5]);
#pragma unroll
    for (int g = 2; g < 8; g += 2) {
      v0 = fmaxf(v0, fmaxf(s[2 * r + 4 * g], s[2 * r + 4 * g + 1]));
      v1 = fmaxf(v1, fmaxf(s[2 * r + 4 * g + 4], s[2 * r + 4 * g + 5]));
    }
    mx[r] = fmaxf(v0, v1) * c;
    need |= !(mx[r] - mc[2 * BLK + r] <= 8.f);
    alpha[r] = 1.f;
  }
  if (__any_sync(0xffffffffu, need)) {
#pragma unroll
    for (int r = 0; r < NR; r++) mx[r] = fmaxf(mx[r], __shfl_xor_sync(0xffffffffu, mx[r], 1));
#pragma unroll
    for (int r = 0; r < NR; r++) mx[r] = fmaxf(mx[r], __shfl_xor_sync(0xffffffffu, mx[r], 2));
#pragma unroll
    for (int r = 0; r < NR; r++) {
      const float mo = mc[2 * BLK + r];
      const float mn = fmaxf(mo, mx[r]);
      alpha[r] = ex2(mo - mn);
      mc[2 * BLK + r] = mn;
      l[2 * BLK + r] *= alpha[r];
    }
    flag = 1;
  }
#pragma unroll
  for (int r = 0; r < NR; r++) {
    const float nm = -mc[2 * BLK + r];
    float sum0 = l[2 * BLK + r], sum1 = 0.f;
#pragma unroll
    for (int g = 0; g < 8; g++) {
      const float p0 = ex2(fmaf(s[2 * r + 4 * g], c, nm));
      const float p1 = ex2(fmaf(s[2 * r + 4 * g + 1], c, nm));
      s[2 * r + 4 * g] = p0;
      s[2 * r + 4 * g + 1] = p1;
      sum0 += p0;
      sum1 += p1;
    }
    const float lr = sum0 + sum1;
    l[2 * BLK + r] = lr;
    alpha[r] = fmaf(lr, 0.f, alpha[r]);
    if (r == 0) mid();
  }
  if (BLK < 2) {
    static_for<0, 4>([&](auto G) {
      constexpr int g = decltype(G)::value;
      const float* q = s + g * 8;
      stsm4_o<(g << 5), BLK * 8192>(cx.pa01, pack_bf16(q[0], q[1]), pack_bf16(q[2], q[3]), pack_bf16(q[4], q[5]),
                                    pack_bf16(q[6], q[7]));
    });
    if (cx.wr) {
      sts32(cx.sa01 + BLK * 64, alpha[0]);
      sts32(cx.sa01 + BLK * 64 + 8, alpha[NR - 1]);
    }
  } else {
    static_for<0, 2>([&](auto G) {
      constexpr int g = decltype(G)::value;
      const float* q = s + g * 16;
      stsm4_o<(g << 6), 0>(cx.pa2, pack_bf16(q[0], q[1]), pack_bf16(q[4], q[5]), pack_bf16(q[8], q[9]),
                           pack_bf16(q[12], q[13]));
    });
    if (cx.wr) sts32(cx.sa2, alpha[0]);
  }
}

__device__ __forceinline__ void s_tile(int j, float* mc, float* l, SCtx& cx, int wi, int lane) {
  constexpr uint32_t sb = SB;
  float sX[32], sY[32];
  uint32_t flag = 0, slot, use;
  const uint32_t pb = j & 1;
  kv_slot(2 * j - 1, slot, use);
  mbar_wait(sb + BAR_FULL + 8 * slot, use & 1);
  const uint32_t dk = dlo(sb + OFF_SLOT) + slot * (SLOT_B >> 4);
  qk_issue<2>(sX, dk);
  qk_issue<0>(sY, dk);
  if (j >= 2) nb_sync(NB_PEMPTY + pb, 384);
  wg_wait<1>();
  reg_fence<32>(sX);
  softmax_blk<2>(sX, mc, l, flag, cx, [] {});
  qk_issue<1>(sX, dk);
  if (j == 1) nb_sync(NB_S, 384);
  nb_arrive(NB_GO, 384);
  if (j == 1) {
    const float4 a = lds128(sb + OFF_ML + (wi * 32 + lane) * 16), bq = lds128(sb + OFF_ML + 2048 + (wi * 32 + lane) * 16);
    mc[0] = a.x; mc[1] = a.y; l[0] = a.z; l[1] = a.w;
    mc[2] = bq.x; mc[3] = bq.y; l[2] = bq.z; l[3] = bq.w;
  }
  wg_wait<1>();
  reg_fence<32>(sY);
  softmax_blk<0>(sY, mc, l, flag, cx, [&] {
    wg_wait<0>();
    if (lane == 0) mbar_arrive_n(sb + BAR_EMPTY + 8 * slot, 2);
  });
  reg_fence<32>(sX);
  softmax_blk<1>(sX, mc, l, flag, cx, [] {});
  if (lane == 0) asm volatile("st.shared.u32 [%0], %1;" ::"r"(sb + OFF_FLAG + pb * 16 + wi * 4), "r"(flag) : "memory");
  fence_async();
  nb_arrive(NB_PFULL + pb, 384);
  const uint32_t dp = pb ? (0u - QCHUNK) : QCHUNK, ds = pb ? (0u - 640u) : 640u;
  cx.pa01 += dp; cx.pa2 += dp; cx.sa01 += ds; cx.sa2 += ds;
}

__global__ void __launch_bounds__(NTHREADS, 1)
fused_gqa_kernel(const __grid_constant__ Maps maps, __nv_bfloat16* __restrict__ out) {
  extern __shared__ uint8_t smem_raw[];
  constexpr uint32_t sb = SB;
  if ((uint32_t)__cvta_generic_to_shared(smem_raw) != sb) __trap();
  const int wg = __shfl_sync(0xffffffffu, threadIdx.x >> 7, 0);
#define ROLE_IDS()                                                   \
  int tid, bid;                                                      \
  asm volatile("mov.u32 %0, %%tid.x;" : "=r"(tid));                  \
  asm volatile("mov.u32 %0, %%ctaid.x;" : "=r"(bid));                \
  const int wi = __shfl_sync(0xffffffffu, (tid >> 5) & 3, 0);        \
  const int lane = tid & 31;                                         \
  const int blk = bid >> 6, kvh = (bid >> 3) & 7, b = bid & 7;       \
  (void)wi; (void)lane; (void)blk; (void)kvh; (void)b

  if (threadIdx.x == 0) {
    for (int s = 0; s < 4; s++) {
      mbar_init(sb + BAR_FULL + 8 * s, 1);
      mbar_init(sb + BAR_EMPTY + 8 * s, 8);
    }
    for (int s = 0; s < 6; s++) {
      mbar_init(sb + BAR_WFULL + 8 * s, 1);
      mbar_init(sb + BAR_WEMPT + 8 * s, 8);
    }
    mbar_init(sb + BAR_T, 1);
    mbar_init(sb + BAR_VL, 1);
    mbar_init(sb + BAR_K0, 12);
    asm volatile("fence.mbarrier_init.release.cluster;" ::: "memory");
    fence_async();
  }
  if (threadIdx.x < 32) {
    nb_arrive(0, 480);
    nb_arrive(15, 64);
    if (threadIdx.x == 0) {
      const int blk = blockIdx.x >> 6, kvh = (blockIdx.x >> 3) & 7, b = blockIdx.x & 7;
      const CUtensorMap* mx0 = &maps.m[blk * 5 + 0];
      const CUtensorMap* mw0 = &maps.m[blk * 5 + 3];
      static_for<0, 2>([&](auto T) {
        constexpr int t = decltype(T)::value, st = (t + 2) % 6, xc = t ? t - 1 : 0;
        constexpr bool hx = (t == 0) || (xc >= 1);
        mbar_expect_tx(sb + BAR_WFULL + 8 * st, hx ? WST_B + 10240 : WST_B);
        if constexpr (t == 0) tma3d(sb + OFF_Q, mx0, b * 80, 0, sb + BAR_WFULL + 8 * st);
        tma3d(sb + OFF_W + st * WST_B, mw0, 16 * t, kvh * 8, sb + BAR_WFULL + 8 * st);
        if constexpr (t > 0 && hx) tma3d(sb + OFF_Q + xc * 10240, mx0, b * 80, xc, sb + BAR_WFULL + 8 * st);
      });
    }
    __syncwarp();
  }

  if (wg == 0) {
    asm volatile("setmaxnreg.dec.sync.aligned.u32 24;");
    ROLE_IDS();
    if (wi == 1) nb_sync(15, 64);
    if (wi > 1) nb_sync(0, 480);
    if (tid == 32) {
      const CUtensorMap* mx0 = &maps.m[blk * 5 + 0];
      const CUtensorMap* mw0 = &maps.m[blk * 5 + 3];
      static_for<2, 6>([&](auto T) {
        constexpr int t = decltype(T)::value, st = (t + 2) % 6, xc = t - 1;
        constexpr bool hx = (xc >= 1);
        mbar_expect_tx(sb + BAR_WFULL + 8 * st, hx ? WST_B + 10240 : WST_B);
        tma3d(sb + OFF_W + st * WST_B, mw0, 16 * t, kvh * 8, sb + BAR_WFULL + 8 * st);
        if constexpr (hx) tma3d(sb + OFF_Q + xc * 10240, mx0, b * 80, xc, sb + BAR_WFULL + 8 * st);
      });
    }
    if (tid >= 64 && tid < 70) {
      const CUtensorMap* m = (tid == 64) ? &maps.k8[blk] : (tid == 68) ? &maps.v16[blk] : (tid == 69) ? &maps.o
                                                         : &maps.m[blk * 5 + (tid == 65 ? 1 : tid == 66 ? 2 : 4)];
      asm volatile("prefetch.tensormap [%0];" ::"l"(m) : "memory");
    }
    if (wi == 3) {
      __nanosleep(20000);
      __nv_bfloat16* o = out + (size_t)(b * 80 + kvh * 10) * 896 + blk * 448;
#pragma unroll 1
      for (int r = 0; r < 10; r++) {
        *reinterpret_cast<uint4*>(o + r * 896 + lane * 8) = make_uint4(0, 0, 0, 0);
        if (lane < 24) *reinterpret_cast<uint4*>(o + r * 896 + 256 + lane * 8) = make_uint4(0, 0, 0, 0);
      }
      __threadfence();
      __syncwarp();
      if (lane == 0) {
        uint32_t old;
        asm volatile("atom.release.gpu.global.add.u32 %0, [%1], 1;" : "=r"(old) : "l"(g_zero + (blk * 8 + b) * 32) : "memory");
        asm volatile("st.shared.u32 [%0], %1;" ::"r"(sb + OFF_MISC), "r"((old | 7u) + 1u) : "memory");
        mbar_arrive(sb + BAR_T);
      }
    }
    if (tid == 0) {
      const CUtensorMap* mk = &maps.m[blk * 5 + 1];
      const CUtensorMap* mv = &maps.m[blk * 5 + 2];
      const CUtensorMap* mwq = &maps.m[blk * 5 + 3];
      const CUtensorMap* mwo = &maps.m[blk * 5 + 4];
      const int row0 = (b * 8 + kvh) * 1024;
      uint32_t tstart, t1 = 0, t2 = 0;
      asm volatile("mov.u32 %0, %%globaltimer_lo;" : "=r"(tstart));
      auto ROW = [&](int j) { return row0 + 64 * (j ^ blk); };
      uint64_t pol;
      asm volatile("createpolicy.fractional.L2::evict_first.b64 %0, 1.0;" : "=l"(pol));
      const CUtensorMap* mx = &maps.m[blk * 5 + 0];
      uint32_t st = 2, ph = 0;
#pragma unroll 1
      for (int t = 6; t < 28; t++) {
        if (t == 6) tma3d_pf(mwq, 16 * (6 + b), kvh * 8);
        if (t == 10) tma3d_pf(mwq, 16 * (14 + b), kvh * 8);
        if (t == 14 && b < 6) tma3d_pf(mwq, 16 * (22 + b), kvh * 8);
        if (t >= 18 && t < 26 && !(t & 1)) {
          const int q = (t - 18) >> 1;
          if (q == 0) mbar_expect_tx(sb + BAR_FULL, SLOT_B);
          tma3d_ef(sb + OFF_SLOT + q * 8192, &maps.k8[blk], ROW(0), q, sb + BAR_FULL, pol);
        }
        mbar_wait(sb + BAR_WEMPT + 8 * st, ph);
        const int xc = t - 1;
        const bool hx = xc < 7;
        mbar_expect_tx(sb + BAR_WFULL + 8 * st, hx ? WST_B + 10240 : WST_B);
        tma3d(sb + OFF_W + st * WST_B, mwq, 16 * t, kvh * 8, sb + BAR_WFULL + 8 * st);
        if (hx) tma3d(sb + OFF_Q + xc * 10240, mx, b * 80, xc, sb + BAR_WFULL + 8 * st);
        if (++st == 6) st = 0;
        if (st == 2) ph ^= 1;
      }
      mbar_wait(sb + BAR_WEMPT, 1);
      mbar_wait(sb + BAR_WEMPT + 8, 1);
      mbar_expect_tx(sb + BAR_FULL + 8, SLOT_B);
      tma3d_ef(sb + OFF_SLOT + SLOT_B, mk, ROW(1), 0, sb + BAR_FULL + 8, pol);
      mbar_wait(sb + BAR_WEMPT + 16, 0);
      mbar_wait(sb + BAR_WEMPT + 24, 0);
#pragma unroll 1
      for (int i = 2; i < 32; i++) {
        uint32_t s, use;
        kv_slot(i, s, use);
        const bool isv = !(i & 1);
        const int j = isv ? ((i - 2) >> 1) : ((i + 1) >> 1);
        if (i == 3) {
          mbar_wait(sb + BAR_K0, 0);
          mbar_arrive_n(sb + BAR_EMPTY, 8);
        }
        if (use > 0) mbar_wait(sb + BAR_EMPTY + 8 * s, (use - 1) & 1);
        {
          uint32_t due = PACE_T0 + i * PACE_TAU, now;
          if (i >= 8) due = max(due, t2 + 2 * PACE_MIN);
          do { asm volatile("mov.u32 %0, %%globaltimer_lo;" : "=r"(now)); } while (now - tstart < due);
          t2 = t1;
          t1 = now - tstart;
        }
        if (i == 31) {
          mbar_expect_tx(sb + BAR_VL, SLOT_B / 2);
          tma3d_ef(sb + OFF_SLOT + s * SLOT_B, &maps.v16[blk], ROW(15), 0, sb + BAR_VL, pol);
          mbar_expect_tx(sb + BAR_FULL + 8 * s, SLOT_B / 2);
          tma3d_ef(sb + OFF_SLOT + s * SLOT_B + SLOT_B / 2, &maps.v16[blk], ROW(15), 2, sb + BAR_FULL + 8 * s, pol);
          break;
        }
        mbar_expect_tx(sb + BAR_FULL + 8 * s, SLOT_B);
        tma3d_ef(sb + OFF_SLOT + s * SLOT_B, isv ? mv : mk, ROW(j), 0, sb + BAR_FULL + 8 * s, pol);
      }
#pragma unroll 1
      for (int u = 0; u < 14; u++) {
        uint32_t s, use;
        wo_slot(u, s, use);
        if (use > 0) mbar_wait(sb + BAR_EMPTY + 8 * s, (use - 1) & 1);
        mbar_expect_tx(sb + BAR_FULL + 8 * s, SLOT_B);
        tma3d(sb + OFF_SLOT + s * SLOT_B, mwo, kvh * 512 + 256 * (u & 1), u >> 1, sb + BAR_FULL + 8 * s);
      }
    }
  } else if (wg == 1) {
    asm volatile("setmaxnreg.dec.sync.aligned.u32 104;");
    nb_sync(0, 480);
    ROLE_IDS();
    float m[5], l[5];
#pragma unroll
    for (int r = 0; r < 5; r++) { m[r] = -INFINITY; l[r] = 0.f; }
    SCtx cx;
    {
      const uint32_t li = lane & 7, lm = lane >> 3;
      cx.pa01 = sb + OFF_P + (16 * wi + li + 8 * (lm & 1)) * 128 + (((lm >> 1) ^ li) << 4);
      cx.pa2 = sb + OFF_P + (128 + 8 * wi + li) * 128 + ((lm ^ li) << 4);
      const uint32_t r8 = lane >> 2;
      cx.sa01 = sb + OFF_SC + (40 * (r8 >> 1) + 2 * (2 * wi) + (r8 & 1)) * 4;
      cx.sa2 = sb + OFF_SC + (40 * (r8 >> 1) + 2 * (16 + wi) + (r8 & 1)) * 4;
      cx.wr = (lane & 3) == 0;
    }
    nb_sync(NB_Q, 384);
    {
      float s0[32];
      uint32_t flag = 0;
      mbar_wait(sb + BAR_FULL, 0);
      qk_issue<2>(s0, dlo(sb + OFF_SLOT));
      nb_arrive(NB_GO, 384);
      wg_wait<0>();
      reg_fence<32>(s0);
      if (lane == 0) mbar_arrive(sb + BAR_K0);
      softmax_blk<2>(s0, m, l, flag, cx, [] {});
      fence_async();
      nb_arrive(NB_PFULL, 384);
      cx.pa01 += QCHUNK; cx.pa2 += QCHUNK; cx.sa01 += 640; cx.sa2 += 640;
    }
#pragma unroll 1
    for (int j = 1; j < 16; j++) s_tile(j, m, l, cx, wi, lane);
#pragma unroll
    for (int r = 0; r < 5; r++) {
      float lr = l[r];
      lr += __shfl_xor_sync(0xffffffffu, lr, 1);
      lr += __shfl_xor_sync(0xffffffffu, lr, 2);
      float inv;
      asm("rcp.approx.ftz.f32 %0, %1;" : "=f"(inv) : "f"(lr));
      if (cx.wr) sts32((r < 4 ? cx.sa01 + (r >> 1) * 64 + (r & 1) * 8 : cx.sa2) + (OFF_LINV - OFF_SC), inv);
    }
    nb_arrive(NB_O2, 384);
    uint32_t tid2, bid2;
    asm volatile("mov.u32 %0, %%tid.x;" : "=r"(tid2));
    asm volatile("mov.u32 %0, %%ctaid.x;" : "=r"(bid2));
    if (tid2 < 160) {
      if (tid2 == 128) {
        uint32_t target, z, it = 0;
        mbar_wait(sb + BAR_T, 0);
        asm volatile("ld.shared.u32 %0, [%1];" : "=r"(target) : "r"(sb + OFF_MISC) : "memory");
        do {
          asm volatile("ld.acquire.gpu.global.u32 %0, [%1];" : "=r"(z) : "l"(g_zero + ((bid2 >> 6) * 8 + (bid2 & 7)) * 32) : "memory");
          if (++it > (1u << 22)) __trap();
        } while ((int)(z - target) < 0);
        asm volatile("fence.proxy.async;" ::: "memory");
      }
#pragma unroll 1
      for (int p = 0; p < 7; p++) {
        nb_sync(NB_SF + (p & 1), 160);
        if (tid2 == 128) {
#pragma unroll
          for (int k = 4; k >= 0; k--) {
            asm volatile("cp.reduce.async.bulk.tensor.3d.global.shared::cta.add.tile.bulk_group [%0, {%1, %2, %3}], [%4];"
                         ::"l"(&maps.o), "r"(0), "r"((bid2 & 7) * 80 + 16 * k), "r"((bid2 >> 6) * 7 + p),
                         "r"(sb + OFF_ST + (k == 4 ? 16384 : (p & 1) * 8192 + k * 2048)) : "memory");
            if (k == 4 || k == 0) asm volatile("cp.async.bulk.commit_group;" ::: "memory");
          }
          asm volatile("cp.async.bulk.wait_group.read 1;" ::: "memory");
        }
        __syncwarp();
        if (p < 6) nb_arrive(nb_se((p + 1) & 1), 160);
        if (tid2 == 128) asm volatile("cp.async.bulk.wait_group.read 0;" ::: "memory");
        __syncwarp();
        if (p < 5) nb_arrive(NB_GO + (p & 1), 160);
      }
    }
  } else {
    asm volatile("setmaxnreg.inc.sync.aligned.u32 192;");
    ROLE_IDS();
    const int w = __shfl_sync(0xffffffffu, (tid >> 7) & 1, 0);
    const uint32_t li = lane & 7, lm = lane >> 3;
    {
      float acc[160];
#pragma unroll
      for (int i = 0; i < 160; i++) acc[i] = 0.f;
      reg_fence<160>(acc);
      nb_sync(0, 480);
      uint32_t st = 2, ph = 0, pst = 0, ok = 0;
#pragma unroll 1
      for (int t = 0; t < 28; t++) {
        if (!ok) mbar_wait(sb + BAR_WFULL + 8 * st, ph);
        const uint32_t nst = (st == 5) ? 0 : st + 1, nph = (nst == 2) ? ph ^ 1 : ph;
        ok = mbar_test(sb + BAR_WFULL + 8 * nst, nph);
        const uint32_t da = dlo(sb + OFF_W) + st * (WST_B >> 4) + w * (8192 >> 4);
        const uint32_t db = dlo(sb + OFF_Q) + (((t >> 2) * 10240 + (t & 3) * 32) >> 4);
        wg_fence();
        static_for<0, 4>([&](auto C) { constexpr int cc = decltype(C)::value; wgmma_n80_mk1<cc * 2048, 0>(acc + 40 * cc, da, db); });
        wg_commit();
        wg_wait<1>();
        if (t > 0 && lane == 0) mbar_arrive(sb + BAR_WEMPT + 8 * pst);
        pst = st;
        st = nst;
        ph = nph;
      }
      wg_wait<0>();
      reg_fence<160>(acc);
      const uint32_t qa = sb + OFF_Q + (80 * w + 8 * (lm >> 1) + li) * 128 + (((2 * wi + (lm & 1)) ^ li) << 4);
#pragma unroll
      for (int cc = 0; cc < 4; cc++) {
        if (cc == 2) nb_sync(NB_O, 256);
#pragma unroll
        for (int jj = 0; jj < 5; jj++) {
          const float* q = acc + 40 * cc + 8 * jj;
          stsm4t(qa + cc * QCHUNK + jj * 2048, pack_bf16(q[0], q[1]), pack_bf16(q[2], q[3]), pack_bf16(q[4], q[5]),
                 pack_bf16(q[6], q[7]));
        }
      }
      fence_async();
      nb_arrive(NB_Q, 384);
    }
    {
      float s0[32], mc[2] = {-INFINITY, -INFINITY}, l[2] = {0.f, 0.f};
      uint32_t flag = 0;
      SCtx cx;
      cx.pa01 = sb + OFF_P + w * 8192 + (16 * wi + li + 8 * (lm & 1)) * 128 + (((lm >> 1) ^ li) << 4);
      cx.sa01 = 0; cx.pa2 = 0; cx.sa2 = 0;
      cx.wr = false;
      mbar_wait(sb + BAR_FULL, 0);
      nb_sync(NB_GO, 384);
      qk_issue<0>(s0, dlo(sb + OFF_SLOT), w * (8192 >> 4));
      wg_wait<0>();
      reg_fence<32>(s0);
      if (lane == 0) mbar_arrive(sb + BAR_K0);
      softmax_blk<0>(s0, mc, l, flag, cx, [] {});
      asm volatile("st.shared.v4.f32 [%0], {%1, %2, %3, %4};" ::"r"(sb + OFF_ML + w * 2048 + (tid & 127) * 16), "f"(mc[0]),
                   "f"(mc[1]), "f"(l[0]), "f"(l[1]) : "memory");
      fence_async();
      nb_arrive(NB_S, 384);
    }
    {
    float acc[160];
#pragma unroll
    for (int i = 0; i < 160; i++) acc[i] = 0.f;
    reg_fence<160>(acc);
#pragma unroll 1
    for (int j = 0; j < 16; j++) {
      const uint32_t pb = j & 1;
      nb_sync(NB_PFULL + pb, 384);
      if (j > 0) {
        const float4 f = lds128(sb + OFF_FLAG + pb * 16);
        if ((__float_as_uint(f.x) | __float_as_uint(f.y) | __float_as_uint(f.z) | __float_as_uint(f.w)) != 0) {
          const uint32_t sc = sb + OFF_SC + pb * 640 + (lane & 3) * 160;
#pragma unroll
          for (int g = 0; g < 10; g++) {
            const float4 a = lds128(sc + g * 16);
#pragma unroll
            for (int mb = 0; mb < 2; mb++) {
              float* q = acc + 80 * mb + 8 * g;
              q[0] *= a.x; q[1] *= a.y; q[2] *= a.x; q[3] *= a.y;
              q[4] *= a.z; q[5] *= a.w; q[6] *= a.z; q[7] *= a.w;
            }
          }
        }
      }
      uint32_t slot, use;
      kv_slot(j == 15 ? 31 : 2 * j + 2, slot, use);
      reg_fence<160>(acc);
      if (j < 15) nb_sync(NB_GO, 384);
      else if (w == 1) nb_sync(NB_O, 256);
      if (j == 15 && w == 0) mbar_wait(sb + BAR_VL, 0);
      else mbar_wait(sb + BAR_FULL + 8 * slot, use & 1);
      const uint32_t da = dlo(sb + OFF_SLOT) + slot * (SLOT_B >> 4) + w * (16384 >> 4);
      const uint32_t db = dlo(sb + OFF_P) + pb * (QCHUNK >> 4);
      wg_fence();
      static_for<0, 4>([&](auto K) {
        constexpr int ks = decltype(K)::value;
        wgmma_n160_mk1<ks * 2048, ks * 32>(acc, da, db);
        wgmma_n160_mk1<8192 + ks * 2048, ks * 32>(acc + 80, da, db);
      });
      wg_commit();
      if (j == 15 && w == 0) nb_arrive(NB_O, 256);
      wg_wait<0>();
      reg_fence<160>(acc);
      if (lane == 0) mbar_arrive(sb + BAR_EMPTY + 8 * slot);
      if (j < 14) nb_arrive(NB_PEMPTY + pb, 384);
    }
    {
      const uint32_t oa = sb + OFF_Q + 2 * w * QCHUNK + (8 * (lm >> 1) + li) * 128 + (((2 * wi + (lm & 1)) ^ li) << 4);
#pragma unroll
      for (int mb = 0; mb < 2; mb++)
#pragma unroll
        for (int jj = 0; jj < 10; jj++) {
          const float* q = acc + 80 * mb + 8 * jj;
          stsm4t(oa + mb * QCHUNK + jj * 2048, pack_bf16(q[0], q[1]), pack_bf16(q[2], q[3]), pack_bf16(q[4], q[5]),
                 pack_bf16(q[6], q[7]));
        }
      fence_async();
    }
    }
    nb_sync(NB_O2, 384);
    constexpr uint32_t dob = dlo(sb + OFF_Q);
    const uint32_t sta = sb + OFF_ST + (8 * (lm >> 1) + li) * 128 + (((2 * wi + (lm & 1)) ^ li) << 4);
    float linv[40];
#pragma unroll
    for (int g = 0; g < 10; g++) {
      const float4 f = lds128(sb + OFF_LINV + (lane & 3) * 160 + g * 16);
      linv[4 * g] = f.x; linv[4 * g + 1] = f.y; linv[4 * g + 2] = f.z; linv[4 * g + 3] = f.w;
    }
#pragma unroll 1
    for (int p = w; p < 7; p += 2) {
      float acc[40], acc1[40];
      uint32_t slot0, use0, slot1, use1;
      wo_slot(2 * p, slot0, use0);
      wo_slot(2 * p + 1, slot1, use1);
      mbar_wait(sb + BAR_FULL + 8 * slot0, use0 & 1);
      if (p > 0) nb_sync(NB_ORD + w, 256);
      uint32_t da = dlo(sb + OFF_SLOT) + slot0 * (SLOT_B >> 4);
      wg_fence();
      wgmma_n80_mk_z<0, 0>(acc, da, dob);
      static_for<1, 9>([&](auto K) {
        constexpr int ks = decltype(K)::value;
        wgmma_n80_mk1<ks * 2048, (ks >> 2) * QCHUNK + (ks & 3) * 32>(acc, da, dob);
      });
      const uint32_t ok1 = mbar_test(sb + BAR_FULL + 8 * slot1, use1 & 1);
      static_for<9, 16>([&](auto K) {
        constexpr int ks = decltype(K)::value;
        wgmma_n80_mk1<ks * 2048, (ks >> 2) * QCHUNK + (ks & 3) * 32>(acc, da, dob);
      });
      wg_commit();
      if (!ok1) mbar_wait(sb + BAR_FULL + 8 * slot1, use1 & 1);
      da = dlo(sb + OFF_SLOT) + slot1 * (SLOT_B >> 4);
      wg_fence();
      wgmma_n80_mk_z<0, 10240>(acc1, da, dob);
      static_for<1, 6>([&](auto K) {
        constexpr int ks = decltype(K)::value;
        wgmma_n80_mk1<ks * 2048, 10240 + (ks >> 2) * QCHUNK + (ks & 3) * 32>(acc1, da, dob);
      });
      wg_commit();
      wg_wait<1>();
      if (lane == 0) mbar_arrive_n(sb + BAR_EMPTY + 8 * slot0, 2);
      wg_fence();
      static_for<6, 16>([&](auto K) {
        constexpr int ks = decltype(K)::value;
        wgmma_n80_mk1<ks * 2048, 10240 + (ks >> 2) * QCHUNK + (ks & 3) * 32>(acc1, da, dob);
      });
      wg_commit();
      if (p < 6) nb_arrive(NB_ORD + (w ^ 1), 256);
      wg_wait<0>();
      reg_fence<40>(acc);
      reg_fence<40>(acc1);
      if (lane == 0) mbar_arrive_n(sb + BAR_EMPTY + 8 * slot1, 2);
#pragma unroll
      for (int i = 0; i < 40; i++)
        acc[i] = fmaf(acc[i], linv[2 * (i >> 2) + (i & 1)], acc1[i] * linv[20 + 2 * (i >> 2) + (i & 1)]);
      uint32_t pk[20];
#pragma unroll
      for (int i = 0; i < 20; i++) pk[i] = pack_bf16(acc[2 * i], acc[2 * i + 1]);
      if (p > 1) nb_sync(NB_GO + w, 160);
#pragma unroll
      for (int k = 0; k < 4; k++) stsm4t(sta + w * 8192 + k * 2048, pk[4 * k], pk[4 * k + 1], pk[4 * k + 2], pk[4 * k + 3]);
      if (p > 0) nb_sync(nb_se(w), 160);
      stsm4t(sta + 16384, pk[16], pk[17], pk[18], pk[19]);
      fence_async();
      nb_arrive(NB_SF + w, 160);
    }
  }
}

typedef CUresult (*EncodeFn)(CUtensorMap*, CUtensorMapDataType, cuuint32_t, void*, const cuuint64_t*, const cuuint64_t*,
                             const cuuint32_t*, const cuuint32_t*, CUtensorMapInterleave, CUtensorMapSwizzle,
                             CUtensorMapL2promotion, CUtensorMapFloatOOBfill);

void encode3d(EncodeFn enc, CUtensorMap* m, void* p, uint64_t rows, uint64_t cols, uint32_t box_rows,
              uint32_t box_blocks) {
  cuuint64_t dims[3] = {64, rows, cols / 64};
  cuuint64_t strides[2] = {cols * 2, 128};
  cuuint32_t box[3] = {64, box_rows, box_blocks};
  cuuint32_t es[3] = {1, 1, 1};
  enc(m, CU_TENSOR_MAP_DATA_TYPE_BFLOAT16, 3, p, dims, strides, box, es, CU_TENSOR_MAP_INTERLEAVE_NONE,
      CU_TENSOR_MAP_SWIZZLE_128B,
      cols == 256 ? CU_TENSOR_MAP_L2_PROMOTION_L2_256B : CU_TENSOR_MAP_L2_PROMOTION_L2_128B,
      CU_TENSOR_MAP_FLOAT_OOB_FILL_NONE);
}

}

extern "C" void kernel_launch(void* const* d_in, const int* in_sizes, int n_in, void* d_out, int out_size) {
  static EncodeFn enc = nullptr;
  if (!enc) {
    void* fn = nullptr;
    cudaDriverEntryPointQueryResult qr;
    cudaGetDriverEntryPoint("cuTensorMapEncodeTiled", &fn, cudaEnableDefault, &qr);
    enc = (EncodeFn)fn;
    cudaFuncSetAttribute(fused_gqa_kernel, cudaFuncAttributeMaxDynamicSharedMemorySize, SMEM_BYTES);
  }
  Maps maps;
  for (int blk = 0; blk < 2; blk++) {
    encode3d(enc, &maps.m[blk * 5 + 0], d_in[blk * 5 + 0], 640, 448, 80, 1);
    encode3d(enc, &maps.m[blk * 5 + 1], d_in[blk * 5 + 1], 65536, 256, 64, 4);
    encode3d(enc, &maps.m[blk * 5 + 2], d_in[blk * 5 + 2], 65536, 256, 64, 4);
    encode3d(enc, &maps.m[blk * 5 + 3], d_in[blk * 5 + 3], 448, 4096, 16, 8);
    encode3d(enc, &maps.m[blk * 5 + 4], d_in[blk * 5 + 4], 4096, 448, 256, 1);
    encode3d(enc, &maps.k8[blk], d_in[blk * 5 + 1], 65536, 256, 64, 1);
    encode3d(enc, &maps.v16[blk], d_in[blk * 5 + 2], 65536, 256, 64, 2);
  }
  encode3d(enc, &maps.o, d_out, 640, 896, 16, 1);
  fused_gqa_kernel<<<NCTA, NTHREADS, SMEM_BYTES>>>(maps, (__nv_bfloat16*)d_out);
}
```

```cpp
#include <cuda_runtime.h>
#include <cuda_bf16.h>
#include <cuda.h>
#include <stdint.h>

namespace {

constexpr int NCTA = 128;
constexpr int NTHREADS = 512;

constexpr uint32_t SB = 0x400;
constexpr uint32_t OFF_Q     = 0;
constexpr uint32_t QCHUNK    = 20480;
constexpr uint32_t OFF_SLOT  = 81920;
constexpr uint32_t SLOT_B    = 32768;
constexpr uint32_t OFF_P     = OFF_SLOT + 3 * SLOT_B;
constexpr uint32_t OFF_W     = OFF_SLOT + SLOT_B;
constexpr uint32_t WST_B     = 16384;
constexpr uint32_t OFF_SC    = OFF_P + 2 * QCHUNK;
constexpr uint32_t OFF_FLAG  = OFF_SC + 1280;
constexpr uint32_t OFF_LINV  = OFF_FLAG + 32;
constexpr uint32_t OFF_ST    = OFF_P + SLOT_B;
constexpr uint32_t OFF_ML    = OFF_ST + 10240;
constexpr uint32_t OFF_BAR   = OFF_ST + 18432;
constexpr uint32_t BAR_FULL  = OFF_BAR;
constexpr uint32_t BAR_EMPTY = BAR_FULL + 32;
constexpr uint32_t BAR_WFULL = BAR_EMPTY + 32;
constexpr uint32_t BAR_WEMPT = BAR_WFULL + 48;
constexpr uint32_t BAR_T     = BAR_WEMPT + 48;
constexpr uint32_t BAR_VL    = BAR_T + 8;
constexpr uint32_t BAR_K0    = BAR_VL + 8;
constexpr uint32_t OFF_MISC  = BAR_K0 + 8;
constexpr uint32_t SMEM_BYTES = OFF_MISC + 16;

#define PACE_TAU 1320
#define PACE_T0 3200
#define PACE_MIN 1250

struct Maps {
  CUtensorMap m[10];
  CUtensorMap k8[2];
  CUtensorMap v16[2];
  CUtensorMap o;
};

__device__ unsigned int g_zero[16 * 32];

__device__ __forceinline__ void mbar_init(uint32_t bar, uint32_t cnt) {
  asm volatile("mbarrier.init.shared::cta.b64 [%0], %1;" ::"r"(bar), "r"(cnt) : "memory");
}
__device__ __forceinline__ void mbar_expect_tx(uint32_t bar, uint32_t bytes) {
  asm volatile("mbarrier.arrive.expect_tx.shared::cta.b64 _, [%0], %1;" ::"r"(bar), "r"(bytes) : "memory");
}
__device__ __forceinline__ void mbar_arrive(uint32_t bar) {
  asm volatile("mbarrier.arrive.shared::cta.b64 _, [%0];" ::"r"(bar) : "memory");
}
__device__ __forceinline__ void mbar_arrive_n(uint32_t bar, uint32_t n) {
  asm volatile("mbarrier.arrive.shared::cta.b64 _, [%0], %1;" ::"r"(bar), "r"(n) : "memory");
}
__device__ __forceinline__ void mbar_wait(uint32_t bar, uint32_t parity) {
  asm volatile(
      "{\n.reg .pred p;\n.reg .u32 c;\nmov.u32 c, 0;\n"
      "W_LOOP:\n"
      "mbarrier.try_wait.parity.shared::cta.b64 p, [%0], %1;\n"
      "@p bra W_DONE;\n"
      "add.u32 c, c, 1;\n"
      "setp.lt.u32 p, c, 0x80000;\n"
      "@p bra W_LOOP;\n"
      "trap;\n"
      "W_DONE:\n}\n" ::"r"(bar), "r"(parity) : "memory");
}
__device__ __forceinline__ uint32_t mbar_test(uint32_t bar, uint32_t parity) {
  uint32_t ok;
  asm volatile("{\n.reg .pred p;\nmbarrier.test_wait.parity.shared::cta.b64 p, [%1], %2;\nselp.u32 %0, 1, 0, p;\n}\n"
               : "=r"(ok) : "r"(bar), "r"(parity) : "memory");
  return ok;
}
__device__ __forceinline__ void nb_sync(uint32_t id, uint32_t n) { asm volatile("bar.sync %0, %1;" ::"r"(id), "r"(n) : "memory"); }
__device__ __forceinline__ void nb_arrive(uint32_t id, uint32_t n) { asm volatile("bar.arrive %0, %1;" ::"r"(id), "r"(n) : "memory"); }
constexpr uint32_t NB_O = 1, NB_PFULL = 2, NB_PEMPTY = 4, NB_GO = 6, NB_Q = 8, NB_INIT = 9, NB_ORD = 10, NB_O2 = 12, NB_S = 13, NB_SF = 14;
__device__ __forceinline__ void init_sync() { asm volatile("barrier.sync %0, 480;" ::"n"(NB_INIT) : "memory"); }
__device__ __forceinline__ uint32_t nb_se(uint32_t w) { return w ? NB_S : NB_Q; }
__device__ __forceinline__ void tma3d(uint32_t dst, const CUtensorMap* m, int c1, int c2, uint32_t bar) {
  asm volatile(
      "cp.async.bulk.tensor.3d.shared::cluster.global.mbarrier::complete_tx::bytes [%0], [%1, {%2, %3, %4}], [%5];"
      ::"r"(dst), "l"(m), "r"(0), "r"(c1), "r"(c2), "r"(bar) : "memory");
}
__device__ __forceinline__ void tma3d_ef(uint32_t dst, const CUtensorMap* m, int c1, int c2, uint32_t bar, uint64_t pol) {
  asm volatile(
      "cp.async.bulk.tensor.3d.shared::cluster.global.mbarrier::complete_tx::bytes.L2::cache_hint [%0], [%1, {%2, %3, %4}], [%5], %6;"
      ::"r"(dst), "l"(m), "r"(0), "r"(c1), "r"(c2), "r"(bar), "l"(pol) : "memory");
}
__device__ __forceinline__ void tma3d_pf(const CUtensorMap* m, int c1, int c2) {
  asm volatile("cp.async.bulk.prefetch.tensor.3d.L2.global [%0, {%1, %2, %3}];" ::"l"(m), "r"(0), "r"(c1), "r"(c2)
               : "memory");
}
__device__ __forceinline__ void wg_fence() { asm volatile("wgmma.fence.sync.aligned;" ::: "memory"); }
__device__ __forceinline__ void wg_commit() { asm volatile("wgmma.commit_group.sync.aligned;" ::: "memory"); }
template <int N>
__device__ __forceinline__ void wg_wait() { asm volatile("wgmma.wait_group.sync.aligned %0;" ::"n"(N) : "memory"); }
__device__ __forceinline__ void fence_async() { asm volatile("fence.proxy.async.shared::cta;" ::: "memory"); }
template <int N>
__device__ __forceinline__ void reg_fence(float* d) {
#pragma unroll
  for (int i = 0; i < N; i++) asm volatile("" : "+f"(d[i])::"memory");
}
__device__ __forceinline__ constexpr uint32_t dlo(uint32_t saddr) { return ((saddr & 0x3FFFFu) >> 4) | (1u << 16); }
template <int V>
struct IC { static constexpr int value = V; };
template <int I, int N, class F>
__device__ __forceinline__ void static_for(F&& f) {
  if constexpr (I < N) {
    f(IC<I>{});
    static_for<I + 1, N>(f);
  }
}
__device__ __forceinline__ uint32_t pack_bf16(float lo, float hi) {
  uint32_t r;
  asm("cvt.rn.bf16x2.f32 %0, %1, %2;" : "=r"(r) : "f"(hi), "f"(lo));
  return r;
}
template <uint32_t XR, uint32_t OFF>
__device__ __forceinline__ void stsm4_o(uint32_t a, uint32_t r0, uint32_t r1, uint32_t r2, uint32_t r3) {
  asm volatile("{\n.reg .b32 t;\nxor.b32 t, %0, %6;\nstmatrix.sync.aligned.m8n8.x4.shared.b16 [t + %5], {%1, %2, %3, %4};\n}\n"
               ::"r"(a), "r"(r0), "r"(r1), "r"(r2), "r"(r3), "n"(OFF), "n"(XR) : "memory");
}
__device__ __forceinline__ void stsm4t(uint32_t a, uint32_t r0, uint32_t r1, uint32_t r2, uint32_t r3) {
  asm volatile("stmatrix.sync.aligned.m8n8.x4.trans.shared.b16 [%0], {%1, %2, %3, %4};" ::"r"(a), "r"(r0), "r"(r1),
               "r"(r2), "r"(r3) : "memory");
}
__device__ __forceinline__ float ex2(float x) {
  float y;
  asm("ex2.approx.ftz.f32 %0, %1;" : "=f"(y) : "f"(x));
  return y;
}
__device__ __forceinline__ float4 lds128(uint32_t a) {
  float4 v;
  asm volatile("ld.shared.v4.f32 {%0, %1, %2, %3}, [%4];" : "=f"(v.x), "=f"(v.y), "=f"(v.z), "=f"(v.w) : "r"(a) : "memory");
  return v;
}
__device__ __forceinline__ void sts32(uint32_t a, float v) {
  asm volatile("st.shared.f32 [%0], %1;" ::"r"(a), "f"(v) : "memory");
}
template <uint32_t OA, uint32_t OB, uint32_t HIA = 0x40000040u>
__device__ __forceinline__ void wgmma_n64_kk_z(float* d, uint32_t a, uint32_t b) {
  asm volatile(
      "{\n.reg .b32 ta, tb;\n.reg .b64 da, db;\nadd.u32 ta, %32, %34;\nadd.u32 tb, %33, %35;\nmov.b64 da, {ta, %36};\nmov.b64 db, {tb, 0x40000040};\n"
      "wgmma.mma_async.sync.aligned.m64n64k16.f32.bf16.bf16 {"
      "%0, %1, %2, %3, %4, %5, %6, %7, %8, %9, %10, %11, %12, %13, %14, %15,"
      "%16, %17, %18, %19, %20, %21, %22, %23, %24, %25, %26, %27, %28, %29, %30, %31}, da, db, 0, 1, 1, 0, 0;\n}\n"
      : "=f"(d[0]), "=f"(d[1]), "=f"(d[2]), "=f"(d[3]), "=f"(d[4]), "=f"(d[5]), "=f"(d[6]), "=f"(d[7]),
        "=f"(d[8]), "=f"(d[9]), "=f"(d[10]), "=f"(d[11]), "=f"(d[12]), "=f"(d[13]), "=f"(d[14]), "=f"(d[15]),
        "=f"(d[16]), "=f"(d[17]), "=f"(d[18]), "=f"(d[19]), "=f"(d[20]), "=f"(d[21]), "=f"(d[22]), "=f"(d[23]),
        "=f"(d[24]), "=f"(d[25]), "=f"(d[26]), "=f"(d[27]), "=f"(d[28]), "=f"(d[29]), "=f"(d[30]), "=f"(d[31])
      : "r"(a), "r"(b), "n"(OA >> 4), "n"(OB >> 4), "n"(HIA));
}

template <uint32_t OA, uint32_t OB, uint32_t HIA = 0x40000040u>
__device__ __forceinline__ void wgmma_n64_kk(float* d, uint32_t a, uint32_t b) {
  asm volatile(
      "{\n.reg .b32 ta, tb;\n.reg .b64 da, db;\nadd.u32 ta, %32, %34;\nadd.u32 tb, %33, %35;\nmov.b64 da, {ta, %36};\nmov.b64 db, {tb, 0x40000040};\n"
      "wgmma.mma_async.sync.aligned.m64n64k16.f32.bf16.bf16 {"
      "%0, %1, %2, %3, %4, %5, %6, %7, %8, %9, %10, %11, %12, %13, %14, %15,"
      "%16, %17, %18, %19, %20, %21, %22, %23, %24, %25, %26, %27, %28, %29, %30, %31}, da, db, 1, 1, 1, 0, 0;\n}\n"
      : "+f"(d[0]), "+f"(d[1]), "+f"(d[2]), "+f"(d[3]), "+f"(d[4]), "+f"(d[5]), "+f"(d[6]), "+f"(d[7]),
        "+f"(d[8]), "+f"(d[9]), "+f"(d[10]), "+f"(d[11]), "+f"(d[12]), "+f"(d[13]), "+f"(d[14]), "+f"(d[15]),
        "+f"(d[16]), "+f"(d[17]), "+f"(d[18]), "+f"(d[19]), "+f"(d[20]), "+f"(d[21]), "+f"(d[22]), "+f"(d[23]),
        "+f"(d[24]), "+f"(d[25]), "+f"(d[26]), "+f"(d[27]), "+f"(d[28]), "+f"(d[29]), "+f"(d[30]), "+f"(d[31])
      : "r"(a), "r"(b), "n"(OA >> 4), "n"(OB >> 4), "n"(HIA));
}

template <uint32_t OA, uint32_t OB, uint32_t HIA = 0x40000040u>
__device__ __forceinline__ void wgmma_n80_mk_z(float* d, uint32_t a, uint32_t b) {
  asm volatile(
      "{\n.reg .b32 ta, tb;\n.reg .b64 da, db;\nadd.u32 ta, %40, %42;\nadd.u32 tb, %41, %43;\nmov.b64 da, {ta, %44};\nmov.b64 db, {tb, 0x40000040};\n"
      "wgmma.mma_async.sync.aligned.m64n80k16.f32.bf16.bf16 {"
      "%0, %1, %2, %3, %4, %5, %6, %7, %8, %9, %10, %11, %12, %13, %14, %15,"
      "%16, %17, %18, %19, %20, %21, %22, %23, %24, %25, %26, %27, %28, %29, %30, %31,"
      "%32, %33, %34, %35, %36, %37, %38, %39}, da, db, 0, 1, 1, 1, 0;\n}\n"
      : "=f"(d[0]), "=f"(d[1]), "=f"(d[2]), "=f"(d[3]), "=f"(d[4]), "=f"(d[5]), "=f"(d[6]), "=f"(d[7]),
        "=f"(d[8]), "=f"(d[9]), "=f"(d[10]), "=f"(d[11]), "=f"(d[12]), "=f"(d[13]), "=f"(d[14]), "=f"(d[15]),
        "=f"(d[16]), "=f"(d[17]), "=f"(d[18]), "=f"(d[19]), "=f"(d[20]), "=f"(d[21]), "=f"(d[22]), "=f"(d[23]),
        "=f"(d[24]), "=f"(d[25]), "=f"(d[26]), "=f"(d[27]), "=f"(d[28]), "=f"(d[29]), "=f"(d[30]), "=f"(d[31]),
        "=f"(d[32]), "=f"(d[33]), "=f"(d[34]), "=f"(d[35]), "=f"(d[36]), "=f"(d[37]), "=f"(d[38]), "=f"(d[39])
      : "r"(a), "r"(b), "n"(OA >> 4), "n"(OB >> 4), "n"(HIA));
}

template <uint32_t OA, uint32_t OB, uint32_t HIA = 0x40000040u>
__device__ __forceinline__ void wgmma_n80_mk1(float* d, uint32_t a, uint32_t b) {
  asm volatile(
      "{\n.reg .b32 ta, tb;\n.reg .b64 da, db;\nadd.u32 ta, %40, %42;\nadd.u32 tb, %41, %43;\nmov.b64 da, {ta, %44};\nmov.b64 db, {tb, 0x40000040};\n"
      "wgmma.mma_async.sync.aligned.m64n80k16.f32.bf16.bf16 {"
      "%0, %1, %2, %3, %4, %5, %6, %7, %8, %9, %10, %11, %12, %13, %14, %15,"
      "%16, %17, %18, %19, %20, %21, %22, %23, %24, %25, %26, %27, %28, %29, %30, %31,"
      "%32, %33, %34, %35, %36, %37, %38, %39}, da, db, 1, 1, 1, 1, 0;\n}\n"
      : "+f"(d[0]), "+f"(d[1]), "+f"(d[2]), "+f"(d[3]), "+f"(d[4]), "+f"(d[5]), "+f"(d[6]), "+f"(d[7]),
        "+f"(d[8]), "+f"(d[9]), "+f"(d[10]), "+f"(d[11]), "+f"(d[12]), "+f"(d[13]), "+f"(d[14]), "+f"(d[15]),
        "+f"(d[16]), "+f"(d[17]), "+f"(d[18]), "+f"(d[19]), "+f"(d[20]), "+f"(d[21]), "+f"(d[22]), "+f"(d[23]),
        "+f"(d[24]), "+f"(d[25]), "+f"(d[26]), "+f"(d[27]), "+f"(d[28]), "+f"(d[29]), "+f"(d[30]), "+f"(d[31]),
        "+f"(d[32]), "+f"(d[33]), "+f"(d[34]), "+f"(d[35]), "+f"(d[36]), "+f"(d[37]), "+f"(d[38]), "+f"(d[39])
      : "r"(a), "r"(b), "n"(OA >> 4), "n"(OB >> 4), "n"(HIA));
}

template <uint32_t OA, uint32_t OB, uint32_t HIA = 0x40000040u>
__device__ __forceinline__ void wgmma_n160_mk1(float* d, uint32_t a, uint32_t b) {
  asm volatile(
      "{\n.reg .b32 ta, tb;\n.reg .b64 da, db;\nadd.u32 ta, %80, %82;\nadd.u32 tb, %81, %83;\nmov.b64 da, {ta, %84};\nmov.b64 db, {tb, 0x40000040};\n"
      "wgmma.mma_async.sync.aligned.m64n160k16.f32.bf16.bf16 {"
      "%0, %1, %2, %3, %4, %5, %6, %7, %8, %9, %10, %11, %12, %13, %14, %15,"
      "%16, %17, %18, %19, %20, %21, %22, %23, %24, %25, %26, %27, %28, %29, %30, %31,"
      "%32, %33, %34, %35, %36, %37, %38, %39, %40, %41, %42, %43, %44, %45, %46, %47,"
      "%48, %49, %50, %51, %52, %53, %54, %55, %56, %57, %58, %59, %60, %61, %62, %63,"
      "%64, %65, %66, %67, %68, %69, %70, %71, %72, %73, %74, %75, %76, %77, %78, %79}, da, db, 1, 1, 1, 1, 0;\n}\n"
      : "+f"(d[0]), "+f"(d[1]), "+f"(d[2]), "+f"(d[3]), "+f"(d[4]), "+f"(d[5]), "+f"(d[6]), "+f"(d[7]),
        "+f"(d[8]), "+f"(d[9]), "+f"(d[10]), "+f"(d[11]), "+f"(d[12]), "+f"(d[13]), "+f"(d[14]), "+f"(d[15]),
        "+f"(d[16]), "+f"(d[17]), "+f"(d[18]), "+f"(d[19]), "+f"(d[20]), "+f"(d[21]), "+f"(d[22]), "+f"(d[23]),
        "+f"(d[24]), "+f"(d[25]), "+f"(d[26]), "+f"(d[27]), "+f"(d[28]), "+f"(d[29]), "+f"(d[30]), "+f"(d[31]),
        "+f"(d[32]), "+f"(d[33]), "+f"(d[34]), "+f"(d[35]), "+f"(d[36]), "+f"(d[37]), "+f"(d[38]), "+f"(d[39]),
        "+f"(d[40]), "+f"(d[41]), "+f"(d[42]), "+f"(d[43]), "+f"(d[44]), "+f"(d[45]), "+f"(d[46]), "+f"(d[47]),
        "+f"(d[48]), "+f"(d[49]), "+f"(d[50]), "+f"(d[51]), "+f"(d[52]), "+f"(d[53]), "+f"(d[54]), "+f"(d[55]),
        "+f"(d[56]), "+f"(d[57]), "+f"(d[58]), "+f"(d[59]), "+f"(d[60]), "+f"(d[61]), "+f"(d[62]), "+f"(d[63]),
        "+f"(d[64]), "+f"(d[65]), "+f"(d[66]), "+f"(d[67]), "+f"(d[68]), "+f"(d[69]), "+f"(d[70]), "+f"(d[71]),
        "+f"(d[72]), "+f"(d[73]), "+f"(d[74]), "+f"(d[75]), "+f"(d[76]), "+f"(d[77]), "+f"(d[78]), "+f"(d[79])
      : "r"(a), "r"(b), "n"(OA >> 4), "n"(OB >> 4), "n"(HIA));
}

__device__ __forceinline__ void kv_slot(int i, uint32_t& slot, uint32_t& use) {
  use = (uint32_t)i / 3u;
  slot = (uint32_t)i - use * 3u;
}
__device__ __forceinline__ void wo_slot(int u, uint32_t& slot, uint32_t& use) {
  uint32_t r = u & 3, q = u >> 2;
  slot = (r == 0) ? 2u : (r == 3) ? 3u : (r - 1u);
  use = q + ((r == 0) ? 10u : (r == 3) ? 0u : 11u);
}

struct SCtx {
  uint32_t pa01, pa2, sa01, sa2;
  bool wr;
};

template <int BLK>
__device__ __forceinline__ void qk_issue(float* s, uint32_t dk, uint32_t qoff = 0) {
  const uint32_t dq = dlo(SB + OFF_Q + BLK * 8192) + qoff;
  constexpr uint32_t HI = (BLK == 2) ? 0x40000020u : 0x40000040u;
  wg_fence();
  constexpr uint32_t T = BLK << 20;
  wgmma_n64_kk_z<0, T, HI>(s, dq, dk);
  static_for<1, 16>([&](auto I) {
    constexpr int ks = decltype(I)::value;
    wgmma_n64_kk<(ks >> 2) * QCHUNK + (ks & 3) * 32, T + (ks >> 2) * 8192 + (ks & 3) * 32, HI>(s, dq, dk);
  });
  wg_commit();
}

template <int BLK, class F>
__device__ __forceinline__ void softmax_blk(float* s, float* mc, float* l, uint32_t& flag, const SCtx& cx, F&& mid) {
  constexpr float c = 0.0625f * 1.4426950408889634f;
  constexpr int NR = (BLK == 2) ? 1 : 2;
  float mx[NR], alpha[NR];
  bool need = false;
#pragma unroll
  for (int r = 0; r < NR; r++) {
    float v0 = fmaxf(s[2 * r], s[2 * r + 1]), v1 = fmaxf(s[2 * r + 4], s[2 * r + 5]);
#pragma unroll
    for (int g = 2; g < 8; g += 2) {
      v0 = fmaxf(v0, fmaxf(s[2 * r + 4 * g], s[2 * r + 4 * g + 1]));
      v1 = fmaxf(v1, fmaxf(s[2 * r + 4 * g + 4], s[2 * r + 4 * g + 5]));
    }
    mx[r] = fmaxf(v0, v1) * c;
    need |= !(mx[r] - mc[2 * BLK + r] <= 8.f);
    alpha[r] = 1.f;
  }
  if (__any_sync(0xffffffffu, need)) {
#pragma unroll
    for (int r = 0; r < NR; r++) mx[r] = fmaxf(mx[r], __shfl_xor_sync(0xffffffffu, mx[r], 1));
#pragma unroll
    for (int r = 0; r < NR; r++) mx[r] = fmaxf(mx[r], __shfl_xor_sync(0xffffffffu, mx[r], 2));
#pragma unroll
    for (int r = 0; r < NR; r++) {
      const float mo = mc[2 * BLK + r];
      const float mn = fmaxf(mo, mx[r]);
      alpha[r] = ex2(mo - mn);
      mc[2 * BLK + r] = mn;
      l[2 * BLK + r] *= alpha[r];
    }
    flag = 1;
  }
#pragma unroll
  for (int r = 0; r < NR; r++) {
    const float nm = -mc[2 * BLK + r];
    float sum0 = l[2 * BLK + r], sum1 = 0.f;
#pragma unroll
    for (int g = 0; g < 8; g++) {
      const float p0 = ex2(fmaf(s[2 * r + 4 * g], c, nm));
      const float p1 = ex2(fmaf(s[2 * r + 4 * g + 1], c, nm));
      s[2 * r + 4 * g] = p0;
      s[2 * r + 4 * g + 1] = p1;
      sum0 += p0;
      sum1 += p1;
    }
    const float lr = sum0 + sum1;
    l[2 * BLK + r] = lr;
    alpha[r] = fmaf(lr, 0.f, alpha[r]);
    if (r == 0) mid();
  }
  if (BLK < 2) {
    static_for<0, 4>([&](auto G) {
      constexpr int g = decltype(G)::value;
      const float* q = s + g * 8;
      stsm4_o<(g << 5), BLK * 8192>(cx.pa01, pack_bf16(q[0], q[1]), pack_bf16(q[2], q[3]), pack_bf16(q[4], q[5]),
                                    pack_bf16(q[6], q[7]));
    });
    if (cx.wr) {
      sts32(cx.sa01 + BLK * 64, alpha[0]);
      sts32(cx.sa01 + BLK * 64 + 8, alpha[NR - 1]);
    }
  } else {
    static_for<0, 2>([&](auto G) {
      constexpr int g = decltype(G)::value;
      const float* q = s + g * 16;
      stsm4_o<(g << 6), 0>(cx.pa2, pack_bf16(q[0], q[1]), pack_bf16(q[4], q[5]), pack_bf16(q[8], q[9]),
                           pack_bf16(q[12], q[13]));
    });
    if (cx.wr) sts32(cx.sa2, alpha[0]);
  }
}

__device__ __forceinline__ void s_tile(int j, float* mc, float* l, SCtx& cx, int wi, int lane) {
  constexpr uint32_t sb = SB;
  float sX[32], sY[32];
  uint32_t flag = 0, slot, use;
  const uint32_t pb = j & 1;
  kv_slot(2 * j - 1, slot, use);
  mbar_wait(sb + BAR_FULL + 8 * slot, use & 1);
  const uint32_t dk = dlo(sb + OFF_SLOT) + slot * (SLOT_B >> 4);
  qk_issue<2>(sX, dk);
  qk_issue<0>(sY, dk);
  if (j >= 2) nb_sync(NB_PEMPTY + pb, 384);
  wg_wait<1>();
  reg_fence<32>(sX);
  softmax_blk<2>(sX, mc, l, flag, cx, [] {});
  qk_issue<1>(sX, dk);
  if (j == 1) nb_sync(NB_S, 384);
  nb_arrive(NB_GO, 384);
  if (j == 1) {
    const float4 a = lds128(sb + OFF_ML + (wi * 32 + lane) * 16), bq = lds128(sb + OFF_ML + 2048 + (wi * 32 + lane) * 16);
    mc[0] = a.x; mc[1] = a.y; l[0] = a.z; l[1] = a.w;
    mc[2] = bq.x; mc[3] = bq.y; l[2] = bq.z; l[3] = bq.w;
  }
  wg_wait<1>();
  reg_fence<32>(sY);
  softmax_blk<0>(sY, mc, l, flag, cx, [&] {
    wg_wait<0>();
    if (lane == 0) mbar_arrive_n(sb + BAR_EMPTY + 8 * slot, 2);
  });
  reg_fence<32>(sX);
  softmax_blk<1>(sX, mc, l, flag, cx, [] {});
  if (lane == 0) asm volatile("st.shared.u32 [%0], %1;" ::"r"(sb + OFF_FLAG + pb * 16 + wi * 4), "r"(flag) : "memory");
  fence_async();
  nb_arrive(NB_PFULL + pb, 384);
  const uint32_t dp = pb ? (0u - QCHUNK) : QCHUNK, ds = pb ? (0u - 640u) : 640u;
  cx.pa01 += dp; cx.pa2 += dp; cx.sa01 += ds; cx.sa2 += ds;
}

__global__ void __launch_bounds__(NTHREADS, 1)
fused_gqa_kernel(const __grid_constant__ Maps maps, __nv_bfloat16* __restrict__ out) {
  extern __shared__ uint8_t smem_raw[];
  constexpr uint32_t sb = SB;
  if ((uint32_t)__cvta_generic_to_shared(smem_raw) != sb) __trap();
  const int wg = __shfl_sync(0xffffffffu, threadIdx.x >> 7, 0);
#define ROLE_IDS()                                                   \
  int tid, bid;                                                      \
  asm volatile("mov.u32 %0, %%tid.x;" : "=r"(tid));                  \
  asm volatile("mov.u32 %0, %%ctaid.x;" : "=r"(bid));                \
  const int wi = __shfl_sync(0xffffffffu, (tid >> 5) & 3, 0);        \
  const int lane = tid & 31;                                         \
  const int blk = bid >> 6, kvh = (bid >> 3) & 7, b = bid & 7;       \
  (void)wi; (void)lane; (void)blk; (void)kvh; (void)b

  if (threadIdx.x == 0) {
    for (int s = 0; s < 4; s++) {
      mbar_init(sb + BAR_FULL + 8 * s, 1);
      mbar_init(sb + BAR_EMPTY + 8 * s, 8);
    }
    for (int s = 0; s < 6; s++) {
      mbar_init(sb + BAR_WFULL + 8 * s, 1);
      mbar_init(sb + BAR_WEMPT + 8 * s, 8);
    }
    mbar_init(sb + BAR_T, 1);
    mbar_init(sb + BAR_VL, 1);
    mbar_init(sb + BAR_K0, 12);
    asm volatile("fence.mbarrier_init.release.cluster;" ::: "memory");
    fence_async();
  }
  if (threadIdx.x < 32) {
    nb_arrive(NB_INIT, 480);
    nb_arrive(15, 64);
    if (threadIdx.x == 0) {
      const int blk = blockIdx.x >> 6, kvh = (blockIdx.x >> 3) & 7, b = blockIdx.x & 7;
      const CUtensorMap* mx0 = &maps.m[blk * 5 + 0];
      const CUtensorMap* mw0 = &maps.m[blk * 5 + 3];
      static_for<0, 2>([&](auto T) {
        constexpr int t = decltype(T)::value, st = (t + 2) % 6, xc = t ? t - 1 : 0;
        constexpr bool hx = (t == 0) || (xc >= 1);
        mbar_expect_tx(sb + BAR_WFULL + 8 * st, hx ? WST_B + 10240 : WST_B);
        if constexpr (t == 0) tma3d(sb + OFF_Q, mx0, b * 80, 0, sb + BAR_WFULL + 8 * st);
        tma3d(sb + OFF_W + st * WST_B, mw0, 16 * t, kvh * 8, sb + BAR_WFULL + 8 * st);
        if constexpr (t > 0 && hx) tma3d(sb + OFF_Q + xc * 10240, mx0, b * 80, xc, sb + BAR_WFULL + 8 * st);
      });
    }
    __syncwarp();
  }

  if (wg == 0) {
    asm volatile("setmaxnreg.dec.sync.aligned.u32 24;");
    ROLE_IDS();
    if (wi == 1) nb_sync(15, 64);
    if (wi > 1) init_sync();
    if (tid == 32) {
      const CUtensorMap* mx0 = &maps.m[blk * 5 + 0];
      const CUtensorMap* mw0 = &maps.m[blk * 5 + 3];
      static_for<2, 6>([&](auto T) {
        constexpr int t = decltype(T)::value, st = (t + 2) % 6, xc = t - 1;
        constexpr bool hx = (xc >= 1);
        mbar_expect_tx(sb + BAR_WFULL + 8 * st, hx ? WST_B + 10240 : WST_B);
        tma3d(sb + OFF_W + st * WST_B, mw0, 16 * t, kvh * 8, sb + BAR_WFULL + 8 * st);
        if constexpr (hx) tma3d(sb + OFF_Q + xc * 10240, mx0, b * 80, xc, sb + BAR_WFULL + 8 * st);
      });
    }
    if (tid >= 64 && tid < 70) {
      const CUtensorMap* m = (tid == 64) ? &maps.k8[blk] : (tid == 68) ? &maps.v16[blk] : (tid == 69) ? &maps.o
                                                         : &maps.m[blk * 5 + (tid == 65 ? 1 : tid == 66 ? 2 : 4)];
      asm volatile("prefetch.tensormap [%0];" ::"l"(m) : "memory");
    }
    if (wi == 3) {
      __nanosleep(20000);
      __nv_bfloat16* o = out + (size_t)(b * 80 + kvh * 10) * 896 + blk * 448;
#pragma unroll 1
      for (int r = 0; r < 10; r++) {
        *reinterpret_cast<uint4*>(o + r * 896 + lane * 8) = make_uint4(0, 0, 0, 0);
        if (lane < 24) *reinterpret_cast<uint4*>(o + r * 896 + 256 + lane * 8) = make_uint4(0, 0, 0, 0);
      }
      __threadfence();
      __syncwarp();
      if (lane == 0) {
        uint32_t old;
        asm volatile("atom.release.gpu.global.add.u32 %0, [%1], 1;" : "=r"(old) : "l"(g_zero + (blk * 8 + b) * 32) : "memory");
        asm volatile("st.shared.u32 [%0], %1;" ::"r"(sb + OFF_MISC), "r"((old | 7u) + 1u) : "memory");
        mbar_arrive(sb + BAR_T);
      }
    }
    if (tid == 0) {
      const CUtensorMap* mk = &maps.m[blk * 5 + 1];
      const CUtensorMap* mv = &maps.m[blk * 5 + 2];
      const CUtensorMap* mwq = &maps.m[blk * 5 + 3];
      const CUtensorMap* mwo = &maps.m[blk * 5 + 4];
      const int row0 = (b * 8 + kvh) * 1024;
      uint32_t tstart, t1 = 0, t2 = 0;
      asm volatile("mov.u32 %0, %%globaltimer_lo;" : "=r"(tstart));
      auto ROW = [&](int j) { return row0 + 64 * (j ^ blk); };
      uint64_t pol;
      asm volatile("createpolicy.fractional.L2::evict_first.b64 %0, 1.0;" : "=l"(pol));
      const CUtensorMap* mx = &maps.m[blk * 5 + 0];
      uint32_t st = 2, ph = 0;
#pragma unroll 1
      for (int t = 6; t < 28; t++) {
        if (t == 6) tma3d_pf(mwq, 16 * (6 + b), kvh * 8);
        if (t == 10) tma3d_pf(mwq, 16 * (14 + b), kvh * 8);
        if (t == 14 && b < 6) tma3d_pf(mwq, 16 * (22 + b), kvh * 8);
        if (t >= 18 && t < 26 && !(t & 1)) {
          const int q = (t - 18) >> 1;
          if (q == 0) mbar_expect_tx(sb + BAR_FULL, SLOT_B);
          tma3d_ef(sb + OFF_SLOT + q * 8192, &maps.k8[blk], ROW(0), q, sb + BAR_FULL, pol);
        }
        mbar_wait(sb + BAR_WEMPT + 8 * st, ph);
        const int xc = t - 1;
        const bool hx = xc < 7;
        mbar_expect_tx(sb + BAR_WFULL + 8 * st, hx ? WST_B + 10240 : WST_B);
        tma3d(sb + OFF_W + st * WST_B, mwq, 16 * t, kvh * 8, sb + BAR_WFULL + 8 * st);
        if (hx) tma3d(sb + OFF_Q + xc * 10240, mx, b * 80, xc, sb + BAR_WFULL + 8 * st);
        if (++st == 6) st = 0;
        if (st == 2) ph ^= 1;
      }
      mbar_wait(sb + BAR_WEMPT, 1);
      mbar_wait(sb + BAR_WEMPT + 8, 1);
      mbar_expect_tx(sb + BAR_FULL + 8, SLOT_B);
      tma3d_ef(sb + OFF_SLOT + SLOT_B, mk, ROW(1), 0, sb + BAR_FULL + 8, pol);
      mbar_wait(sb + BAR_WEMPT + 16, 0);
      mbar_wait(sb + BAR_WEMPT + 24, 0);
#pragma unroll 1
      for (int i = 2; i < 32; i++) {
        uint32_t s, use;
        kv_slot(i, s, use);
        const bool isv = !(i & 1);
        const int j = isv ? ((i - 2) >> 1) : ((i + 1) >> 1);
        if (i == 3) {
          mbar_wait(sb + BAR_K0, 0);
          mbar_arrive_n(sb + BAR_EMPTY, 8);
        }
        if (use > 0) mbar_wait(sb + BAR_EMPTY + 8 * s, (use - 1) & 1);
        {
          uint32_t due = PACE_T0 + i * PACE_TAU, now;
          if (i >= 8) due = max(due, t2 + 2 * PACE_MIN);
          do { asm volatile("mov.u32 %0, %%globaltimer_lo;" : "=r"(now)); } while (now - tstart < due);
          t2 = t1;
          t1 = now - tstart;
        }
        if (i == 31) {
          mbar_expect_tx(sb + BAR_VL, SLOT_B / 2);
          tma3d_ef(sb + OFF_SLOT + s * SLOT_B, &maps.v16[blk], ROW(15), 0, sb + BAR_VL, pol);
          mbar_expect_tx(sb + BAR_FULL + 8 * s, SLOT_B / 2);
          tma3d_ef(sb + OFF_SLOT + s * SLOT_B + SLOT_B / 2, &maps.v16[blk], ROW(15), 2, sb + BAR_FULL + 8 * s, pol);
          break;
        }
        mbar_expect_tx(sb + BAR_FULL + 8 * s, SLOT_B);
        tma3d_ef(sb + OFF_SLOT + s * SLOT_B, isv ? mv : mk, ROW(j), 0, sb + BAR_FULL + 8 * s, pol);
      }
#pragma unroll 1
      for (int u = 0; u < 14; u++) {
        uint32_t s, use;
        wo_slot(u, s, use);
        if (use > 0) mbar_wait(sb + BAR_EMPTY + 8 * s, (use - 1) & 1);
        mbar_expect_tx(sb + BAR_FULL + 8 * s, SLOT_B);
        tma3d(sb + OFF_SLOT + s * SLOT_B, mwo, kvh * 512 + 256 * (u & 1), u >> 1, sb + BAR_FULL + 8 * s);
      }
    }
  } else if (wg == 1) {
    asm volatile("setmaxnreg.dec.sync.aligned.u32 104;");
    init_sync();
    ROLE_IDS();
    float m[5], l[5];
#pragma unroll
    for (int r = 0; r < 5; r++) { m[r] = -INFINITY; l[r] = 0.f; }
    SCtx cx;
    {
      const uint32_t li = lane & 7, lm = lane >> 3;
      cx.pa01 = sb + OFF_P + (16 * wi + li + 8 * (lm & 1)) * 128 + (((lm >> 1) ^ li) << 4);
      cx.pa2 = sb + OFF_P + (128 + 8 * wi + li) * 128 + ((lm ^ li) << 4);
      const uint32_t r8 = lane >> 2;
      cx.sa01 = sb + OFF_SC + (40 * (r8 >> 1) + 2 * (2 * wi) + (r8 & 1)) * 4;
      cx.sa2 = sb + OFF_SC + (40 * (r8 >> 1) + 2 * (16 + wi) + (r8 & 1)) * 4;
      cx.wr = (lane & 3) == 0;
    }
    nb_sync(NB_Q, 384);
    {
      float s0[32];
      uint32_t flag = 0;
      mbar_wait(sb + BAR_FULL, 0);
      qk_issue<2>(s0, dlo(sb + OFF_SLOT));
      nb_arrive(NB_GO, 384);
      wg_wait<0>();
      reg_fence<32>(s0);
      if (lane == 0) mbar_arrive(sb + BAR_K0);
      softmax_blk<2>(s0, m, l, flag, cx, [] {});
      fence_async();
      nb_arrive(NB_PFULL, 384);
      cx.pa01 += QCHUNK; cx.pa2 += QCHUNK; cx.sa01 += 640; cx.sa2 += 640;
    }
#pragma unroll 1
    for (int j = 1; j < 16; j++) s_tile(j, m, l, cx, wi, lane);
#pragma unroll
    for (int r = 0; r < 5; r++) {
      float lr = l[r];
      lr += __shfl_xor_sync(0xffffffffu, lr, 1);
      lr += __shfl_xor_sync(0xffffffffu, lr, 2);
      float inv;
      asm("rcp.approx.ftz.f32 %0, %1;" : "=f"(inv) : "f"(lr));
      if (cx.wr) sts32((r < 4 ? cx.sa01 + (r >> 1) * 64 + (r & 1) * 8 : cx.sa2) + (OFF_LINV - OFF_SC), inv);
    }
    nb_arrive(NB_O2, 384);
    uint32_t tid2, bid2;
    asm volatile("mov.u32 %0, %%tid.x;" : "=r"(tid2));
    asm volatile("mov.u32 %0, %%ctaid.x;" : "=r"(bid2));
    if (tid2 < 160) {
      if (tid2 == 128) {
        uint32_t target, z, it = 0;
        mbar_wait(sb + BAR_T, 0);
        asm volatile("ld.shared.u32 %0, [%1];" : "=r"(target) : "r"(sb + OFF_MISC) : "memory");
        do {
          asm volatile("ld.acquire.gpu.global.u32 %0, [%1];" : "=r"(z) : "l"(g_zero + ((bid2 >> 6) * 8 + (bid2 & 7)) * 32) : "memory");
          if (++it > (1u << 22)) __trap();
        } while ((int)(z - target) < 0);
        asm volatile("fence.proxy.async;" ::: "memory");
      }
#pragma unroll 1
      for (int p = 0; p < 7; p++) {
        nb_sync(NB_SF + (p & 1), 160);
        if (tid2 == 128) {
#pragma unroll
          for (int k = 4; k >= 0; k--) {
            asm volatile("cp.reduce.async.bulk.tensor.3d.global.shared::cta.add.tile.bulk_group [%0, {%1, %2, %3}], [%4];"
                         ::"l"(&maps.o), "r"(0), "r"((bid2 & 7) * 80 + 16 * k), "r"((bid2 >> 6) * 7 + p),
                         "r"(sb + OFF_ST + (k == 4 ? 16384 : (p & 1) * 8192 + k * 2048)) : "memory");
            if (k == 4 || k == 0) asm volatile("cp.async.bulk.commit_group;" ::: "memory");
          }
          asm volatile("cp.async.bulk.wait_group.read 1;" ::: "memory");
        }
        __syncwarp();
        if (p < 6) nb_arrive(nb_se((p + 1) & 1), 160);
        if (tid2 == 128) asm volatile("cp.async.bulk.wait_group.read 0;" ::: "memory");
        __syncwarp();
        if (p < 5) nb_arrive(NB_GO + (p & 1), 160);
      }
    }
  } else {
    asm volatile("setmaxnreg.inc.sync.aligned.u32 192;");
    ROLE_IDS();
    const int w = __shfl_sync(0xffffffffu, (tid >> 7) & 1, 0);
    const uint32_t li = lane & 7, lm = lane >> 3;
    {
      float acc[160];
#pragma unroll
      for (int i = 0; i < 160; i++) acc[i] = 0.f;
      reg_fence<160>(acc);
      init_sync();
      uint32_t st = 2, ph = 0, pst = 0, ok = 0;
#pragma unroll 1
      for (int t = 0; t < 28; t++) {
        if (!ok) mbar_wait(sb + BAR_WFULL + 8 * st, ph);
        const uint32_t nst = (st == 5) ? 0 : st + 1, nph = (nst == 2) ? ph ^ 1 : ph;
        ok = mbar_test(sb + BAR_WFULL + 8 * nst, nph);
        const uint32_t da = dlo(sb + OFF_W) + st * (WST_B >> 4) + w * (8192 >> 4);
        const uint32_t db = dlo(sb + OFF_Q) + (((t >> 2) * 10240 + (t & 3) * 32) >> 4);
        wg_fence();
        static_for<0, 4>([&](auto C) { constexpr int cc = decltype(C)::value; wgmma_n80_mk1<cc * 2048, 0>(acc + 40 * cc, da, db); });
        wg_commit();
        wg_wait<1>();
        if (t > 0 && lane == 0) mbar_arrive(sb + BAR_WEMPT + 8 * pst);
        pst = st;
        st = nst;
        ph = nph;
      }
      wg_wait<0>();
      reg_fence<160>(acc);
      const uint32_t qa = sb + OFF_Q + (80 * w + 8 * (lm >> 1) + li) * 128 + (((2 * wi + (lm & 1)) ^ li) << 4);
#pragma unroll
      for (int cc = 0; cc < 4; cc++) {
        if (cc == 2) nb_sync(NB_O, 256);
#pragma unroll
        for (int jj = 0; jj < 5; jj++) {
          const float* q = acc + 40 * cc + 8 * jj;
          stsm4t(qa + cc * QCHUNK + jj * 2048, pack_bf16(q[0], q[1]), pack_bf16(q[2], q[3]), pack_bf16(q[4], q[5]),
                 pack_bf16(q[6], q[7]));
        }
      }
      fence_async();
      nb_arrive(NB_Q, 384);
    }
    {
      float s0[32], mc[2] = {-INFINITY, -INFINITY}, l[2] = {0.f, 0.f};
      uint32_t flag = 0;
      SCtx cx;
      cx.pa01 = sb + OFF_P + w * 8192 + (16 * wi + li + 8 * (lm & 1)) * 128 + (((lm >> 1) ^ li) << 4);
      cx.sa01 = 0; cx.pa2 = 0; cx.sa2 = 0;
      cx.wr = false;
      mbar_wait(sb + BAR_FULL, 0);
      nb_sync(NB_GO, 384);
      qk_issue<0>(s0, dlo(sb + OFF_SLOT), w * (8192 >> 4));
      wg_wait<0>();
      reg_fence<32>(s0);
      if (lane == 0) mbar_arrive(sb + BAR_K0);
      softmax_blk<0>(s0, mc, l, flag, cx, [] {});
      asm volatile("st.shared.v4.f32 [%0], {%1, %2, %3, %4};" ::"r"(sb + OFF_ML + w * 2048 + (tid & 127) * 16), "f"(mc[0]),
                   "f"(mc[1]), "f"(l[0]), "f"(l[1]) : "memory");
      fence_async();
      nb_arrive(NB_S, 384);
    }
    {
    float acc[160];
#pragma unroll
    for (int i = 0; i < 160; i++) acc[i] = 0.f;
    reg_fence<160>(acc);
#pragma unroll 1
    for (int j = 0; j < 16; j++) {
      const uint32_t pb = j & 1;
      nb_sync(NB_PFULL + pb, 384);
      if (j > 0) {
        const float4 f = lds128(sb + OFF_FLAG + pb * 16);
        if ((__float_as_uint(f.x) | __float_as_uint(f.y) | __float_as_uint(f.z) | __float_as_uint(f.w)) != 0) {
          const uint32_t sc = sb + OFF_SC + pb * 640 + (lane & 3) * 160;
#pragma unroll
          for (int g = 0; g < 10; g++) {
            const float4 a = lds128(sc + g * 16);
#pragma unroll
            for (int mb = 0; mb < 2; mb++) {
              float* q = acc + 80 * mb + 8 * g;
              q[0] *= a.x; q[1] *= a.y; q[2] *= a.x; q[3] *= a.y;
              q[4] *= a.z; q[5] *= a.w; q[6] *= a.z; q[7] *= a.w;
            }
          }
        }
      }
      uint32_t slot, use;
      kv_slot(j == 15 ? 31 : 2 * j + 2, slot, use);
      reg_fence<160>(acc);
      if (j < 15) nb_sync(NB_GO, 384);
      else if (w == 1) nb_sync(NB_O, 256);
      if (j == 15 && w == 0) mbar_wait(sb + BAR_VL, 0);
      else mbar_wait(sb + BAR_FULL + 8 * slot, use & 1);
      const uint32_t da = dlo(sb + OFF_SLOT) + slot * (SLOT_B >> 4) + w * (16384 >> 4);
      const uint32_t db = dlo(sb + OFF_P) + pb * (QCHUNK >> 4);
      wg_fence();
      static_for<0, 4>([&](auto K) {
        constexpr int ks = decltype(K)::value;
        wgmma_n160_mk1<ks * 2048, ks * 32>(acc, da, db);
        wgmma_n160_mk1<8192 + ks * 2048, ks * 32>(acc + 80, da, db);
      });
      wg_commit();
      if (j == 15 && w == 0) nb_arrive(NB_O, 256);
      wg_wait<0>();
      reg_fence<160>(acc);
      if (lane == 0) mbar_arrive(sb + BAR_EMPTY + 8 * slot);
      if (j < 14) nb_arrive(NB_PEMPTY + pb, 384);
    }
    {
      const uint32_t oa = sb + OFF_Q + 2 * w * QCHUNK + (8 * (lm >> 1) + li) * 128 + (((2 * wi + (lm & 1)) ^ li) << 4);
#pragma unroll
      for (int mb = 0; mb < 2; mb++)
#pragma unroll
        for (int jj = 0; jj < 10; jj++) {
          const float* q = acc + 80 * mb + 8 * jj;
          stsm4t(oa + mb * QCHUNK + jj * 2048, pack_bf16(q[0], q[1]), pack_bf16(q[2], q[3]), pack_bf16(q[4], q[5]),
                 pack_bf16(q[6], q[7]));
        }
      fence_async();
    }
    }
    nb_sync(NB_O2, 384);
    constexpr uint32_t dob = dlo(sb + OFF_Q);
    const uint32_t sta = sb + OFF_ST + (8 * (lm >> 1) + li) * 128 + (((2 * wi + (lm & 1)) ^ li) << 4);
    float linv[40];
#pragma unroll
    for (int g = 0; g < 10; g++) {
      const float4 f = lds128(sb + OFF_LINV + (lane & 3) * 160 + g * 16);
      linv[4 * g] = f.x; linv[4 * g + 1] = f.y; linv[4 * g + 2] = f.z; linv[4 * g + 3] = f.w;
    }
#pragma unroll 1
    for (int p = w; p < 7; p += 2) {
      float acc[40], acc1[40];
      uint32_t slot0, use0, slot1, use1;
      wo_slot(2 * p, slot0, use0);
      wo_slot(2 * p + 1, slot1, use1);
      mbar_wait(sb + BAR_FULL + 8 * slot0, use0 & 1);
      if (p > 0) nb_sync(NB_ORD + w, 256);
      uint32_t da = dlo(sb + OFF_SLOT) + slot0 * (SLOT_B >> 4);
      wg_fence();
      wgmma_n80_mk_z<0, 0>(acc, da, dob);
      static_for<1, 9>([&](auto K) {
        constexpr int ks = decltype(K)::value;
        wgmma_n80_mk1<ks * 2048, (ks >> 2) * QCHUNK + (ks & 3) * 32>(acc, da, dob);
      });
      const uint32_t ok1 = mbar_test(sb + BAR_FULL + 8 * slot1, use1 & 1);
      static_for<9, 16>([&](auto K) {
        constexpr int ks = decltype(K)::value;
        wgmma_n80_mk1<ks * 2048, (ks >> 2) * QCHUNK + (ks & 3) * 32>(acc, da, dob);
      });
      wg_commit();
      if (!ok1) mbar_wait(sb + BAR_FULL + 8 * slot1, use1 & 1);
      da = dlo(sb + OFF_SLOT) + slot1 * (SLOT_B >> 4);
      wg_fence();
      wgmma_n80_mk_z<0, 10240>(acc1, da, dob);
      static_for<1, 6>([&](auto K) {
        constexpr int ks = decltype(K)::value;
        wgmma_n80_mk1<ks * 2048, 10240 + (ks >> 2) * QCHUNK + (ks & 3) * 32>(acc1, da, dob);
      });
      wg_commit();
      wg_wait<1>();
      if (lane == 0) mbar_arrive_n(sb + BAR_EMPTY + 8 * slot0, 2);
      wg_fence();
      static_for<6, 16>([&](auto K) {
        constexpr int ks = decltype(K)::value;
        wgmma_n80_mk1<ks * 2048, 10240 + (ks >> 2) * QCHUNK + (ks & 3) * 32>(acc1, da, dob);
      });
      wg_commit();
      if (p < 6) nb_arrive(NB_ORD + (w ^ 1), 256);
      wg_wait<0>();
      reg_fence<40>(acc);
      reg_fence<40>(acc1);
      if (lane == 0) mbar_arrive_n(sb + BAR_EMPTY + 8 * slot1, 2);
#pragma unroll
      for (int i = 0; i < 40; i++)
        acc[i] = fmaf(acc[i], linv[2 * (i >> 2) + (i & 1)], acc1[i] * linv[20 + 2 * (i >> 2) + (i & 1)]);
      uint32_t pk[20];
#pragma unroll
      for (int i = 0; i < 20; i++) pk[i] = pack_bf16(acc[2 * i], acc[2 * i + 1]);
      if (p > 1) nb_sync(NB_GO + w, 160);
#pragma unroll
      for (int k = 0; k < 4; k++) stsm4t(sta + w * 8192 + k * 2048, pk[4 * k], pk[4 * k + 1], pk[4 * k + 2], pk[4 * k + 3]);
      if (p > 0) nb_sync(nb_se(w), 160);
      stsm4t(sta + 16384, pk[16], pk[17], pk[18], pk[19]);
      fence_async();
      nb_arrive(NB_SF + w, 160);
    }
  }
}

typedef CUresult (*EncodeFn)(CUtensorMap*, CUtensorMapDataType, cuuint32_t, void*, const cuuint64_t*, const cuuint64_t*,
                             const cuuint32_t*, const cuuint32_t*, CUtensorMapInterleave, CUtensorMapSwizzle,
                             CUtensorMapL2promotion, CUtensorMapFloatOOBfill);

void encode3d(EncodeFn enc, CUtensorMap* m, void* p, uint64_t rows, uint64_t cols, uint32_t box_rows,
              uint32_t box_blocks) {
  cuuint64_t dims[3] = {64, rows, cols / 64};
  cuuint64_t strides[2] = {cols * 2, 128};
  cuuint32_t box[3] = {64, box_rows, box_blocks};
  cuuint32_t es[3] = {1, 1, 1};
  enc(m, CU_TENSOR_MAP_DATA_TYPE_BFLOAT16, 3, p, dims, strides, box, es, CU_TENSOR_MAP_INTERLEAVE_NONE,
      CU_TENSOR_MAP_SWIZZLE_128B,
      cols == 256 ? CU_TENSOR_MAP_L2_PROMOTION_L2_256B : CU_TENSOR_MAP_L2_PROMOTION_L2_128B,
      CU_TENSOR_MAP_FLOAT_OOB_FILL_NONE);
}

}

extern "C" void kernel_launch(void* const* d_in, const int* in_sizes, int n_in, void* d_out, int out_size) {
  static EncodeFn enc = nullptr;
  if (!enc) {
    void* fn = nullptr;
    cudaDriverEntryPointQueryResult qr;
    cudaGetDriverEntryPoint("cuTensorMapEncodeTiled", &fn, cudaEnableDefault, &qr);
    enc = (EncodeFn)fn;
    cudaFuncSetAttribute(fused_gqa_kernel, cudaFuncAttributeMaxDynamicSharedMemorySize, SMEM_BYTES);
  }
  Maps maps;
  for (int blk = 0; blk < 2; blk++) {
    encode3d(enc, &maps.m[blk * 5 + 0], d_in[blk * 5 + 0], 640, 448, 80, 1);
    encode3d(enc, &maps.m[blk * 5 + 1], d_in[blk * 5 + 1], 65536, 256, 64, 4);
    encode3d(enc, &maps.m[blk * 5 + 2], d_in[blk * 5 + 2], 65536, 256, 64, 4);
    encode3d(enc, &maps.m[blk * 5 + 3], d_in[blk * 5 + 3], 448, 4096, 16, 8);
    encode3d(enc, &maps.m[blk * 5 + 4], d_in[blk * 5 + 4], 4096, 448, 256, 1);
    encode3d(enc, &maps.k8[blk], d_in[blk * 5 + 1], 65536, 256, 64, 1);
    encode3d(enc, &maps.v16[blk], d_in[blk * 5 + 2], 65536, 256, 64, 2);
  }
  encode3d(enc, &maps.o, d_out, 640, 896, 16, 1);
  fused_gqa_kernel<<<NCTA, NTHREADS, SMEM_BYTES>>>(maps, (__nv_bfloat16*)d_out);
}
```
